```python
import torch

def _softmax(x, axis=-1):
    return torch.softmax(x, dim=axis)
def _gelu(x):
    return torch.nn.functional.gelu(x, approximate="tanh")
def _silu(x):
    return torch.nn.functional.silu(x)
def _sigmoid(x):
    return torch.sigmoid(x)
def _layernorm(x, axis=-1, eps=1e-5):
    m = x.mean(dim=axis, keepdim=True)
    v = x.var(dim=axis, keepdim=True, unbiased=False)
    return (x - m) / torch.sqrt(v + eps)
def _scatter_add(tgt, idx, src, axis=0):
    return tgt.clone().index_add_(axis, idx, src)
def _segment_sum(src, seg, n):
    out = torch.zeros((n,) + src.shape[1:], dtype=src.dtype)
    return out.index_add_(0, seg, src)
def _pad(x, pw):
    flat = tuple(v for pair in reversed(pw) for v in pair)
    return torch.nn.functional.pad(x, flat)

kernel_name = 'sequential_preLN__ssm_conv_h3__swiglu_ffn__prompt'

def setup_inputs():

    _w = (lambda a: (lambda t: t.to(torch.bfloat16) if t.is_floating_point() else t)(torch.as_tensor(a)))
    def _A_setup():
        B, S, D = 1, 2048, 512
        ks = 4
        return {
            "q": _w((lambda *s: torch.randn(*s, dtype=torch.bfloat16) * 0.05)(B, S, D)),
            "k": _w((lambda *s: torch.randn(*s, dtype=torch.bfloat16) * 0.4)(B, S, D)),
            "v": _w((lambda *s: torch.randn(*s, dtype=torch.bfloat16) * 0.4)(B, S, D)),
            "shift_k": _w((lambda *s: torch.randn(*s, dtype=torch.bfloat16) * 0.4)(D, ks) * 0.5),
            "ssm_k": _w((lambda *s: torch.randn(*s, dtype=torch.bfloat16) * 0.4)(D, S) * (1.0 / S ** 0.5)),
            "ssm_D": _w((lambda *s: torch.randn(*s, dtype=torch.bfloat16) * 0.4)(D)),
        }
    _A_in = _A_setup()

    def _B_setup():
        B, S, D, F = 1, 2048, 512, 1376
        return {
            "x": _w((lambda *s: torch.randn(*s, dtype=torch.bfloat16) * 0.05)(B, S, D)),
            "w_gate": _w((lambda *s: torch.randn(*s, dtype=torch.bfloat16) * 0.05)(D, F)),
            "w_up": _w((lambda *s: torch.randn(*s, dtype=torch.bfloat16) * 0.05)(D, F)),
            "w_down": _w((lambda *s: torch.randn(*s, dtype=torch.bfloat16) * 0.05)(F, D)),
        }
    _B_in = _B_setup()

    return {
        "A_q": _A_in["q"],
        "A_k": _A_in["k"],
        "A_v": _A_in["v"],
        "A_shift_k": _A_in["shift_k"],
        "A_ssm_k": _A_in["ssm_k"],
        "A_ssm_D": _A_in["ssm_D"],
        "B_x": _B_in["x"],
        "B_w_gate": _B_in["w_gate"],
        "B_w_up": _B_in["w_up"],
        "B_w_down": _B_in["w_down"],
    }

def reference(A_q, A_k, A_v, A_shift_k, A_ssm_k, A_ssm_D, B_x, B_w_gate, B_w_up, B_w_down):
    def _A_ref(q, k, v, shift_k, ssm_k, ssm_D):
        B, S, D = q.shape
        ks = shift_k.shape[-1]
        k_pad = _pad(k, ((0, 0), (ks - 1, 0), (0, 0)))
        k_shift = torch.zeros_like(k)
        for t in range(ks):
            k_shift = k_shift + k_pad[:, t:t + S, :] * shift_k[:, ks - 1 - t][None, None, :]
        kv = k_shift * v
        L = 2 * S
        kv_pad = _pad(kv, ((0, 0), (0, S), (0, 0)))
        kf_pad = _pad(ssm_k, ((0, 0), (0, S)))
        kv_f = (lambda x, axes=(-2,-1): torch.fft.rfft2(x.float(), dim=axes))(kv_pad[:, None, :, :], axes=(1, 2))
        kf_f = (lambda x, axes=(-2,-1): torch.fft.rfft2(x.float(), dim=axes))(kf_pad[:, None, :], axes=(1, 2))
        kf_f = (lambda x, *d: x.permute(*d))(kf_f, 1, 2, 0)
        y_f = kv_f * kf_f[None, :, :, :]
        y = (lambda x, s, axes=(-2,-1): torch.fft.irfft2(x, s=s, dim=axes).to(torch.bfloat16))(y_f, (1, L), axes=(1, 2))[:, 0, :S, :]
        y = y + kv * ssm_D[None, None, :]
        return q * y

    def _B_ref(x, w_gate, w_up, w_down):
        g = _silu(x @ w_gate)
        u = x @ w_up
        return (g * u) @ w_down

    x = A_q
    h = x + _A_ref(_layernorm(x, axis=-1), A_k, A_v, A_shift_k, A_ssm_k, A_ssm_D)
    h2 = h + _B_ref(_layernorm(h, axis=-1), B_w_gate, B_w_up, B_w_down)
    return h2
```

```cpp
#include <cuda_runtime.h>
#include <cuda_bf16.h>
#include <cuda.h>
#include <stdint.h>

template<int TA,int TB> __device__ __forceinline__ void wgmma_ss_n176(float* d, uint64_t da, uint64_t db, int sd){
  asm volatile("{ .reg .pred p; setp.ne.b32 p, %90, 0; wgmma.mma_async.sync.aligned.m64n176k16.f32.bf16.bf16 {%0,%1,%2,%3,%4,%5,%6,%7,%8,%9,%10,%11,%12,%13,%14,%15,%16,%17,%18,%19,%20,%21,%22,%23,%24,%25,%26,%27,%28,%29,%30,%31,%32,%33,%34,%35,%36,%37,%38,%39,%40,%41,%42,%43,%44,%45,%46,%47,%48,%49,%50,%51,%52,%53,%54,%55,%56,%57,%58,%59,%60,%61,%62,%63,%64,%65,%66,%67,%68,%69,%70,%71,%72,%73,%74,%75,%76,%77,%78,%79,%80,%81,%82,%83,%84,%85,%86,%87}, %88, %89, p, 1, 1, %91, %92; }"
   : "+f"(d[0]),"+f"(d[1]),"+f"(d[2]),"+f"(d[3]),"+f"(d[4]),"+f"(d[5]),"+f"(d[6]),"+f"(d[7]),"+f"(d[8]),"+f"(d[9]),"+f"(d[10]),"+f"(d[11]),"+f"(d[12]),"+f"(d[13]),"+f"(d[14]),"+f"(d[15]),"+f"(d[16]),"+f"(d[17]),"+f"(d[18]),"+f"(d[19]),"+f"(d[20]),"+f"(d[21]),"+f"(d[22]),"+f"(d[23]),"+f"(d[24]),"+f"(d[25]),"+f"(d[26]),"+f"(d[27]),"+f"(d[28]),"+f"(d[29]),"+f"(d[30]),"+f"(d[31]),"+f"(d[32]),"+f"(d[33]),"+f"(d[34]),"+f"(d[35]),"+f"(d[36]),"+f"(d[37]),"+f"(d[38]),"+f"(d[39]),"+f"(d[40]),"+f"(d[41]),"+f"(d[42]),"+f"(d[43]),"+f"(d[44]),"+f"(d[45]),"+f"(d[46]),"+f"(d[47]),"+f"(d[48]),"+f"(d[49]),"+f"(d[50]),"+f"(d[51]),"+f"(d[52]),"+f"(d[53]),"+f"(d[54]),"+f"(d[55]),"+f"(d[56]),"+f"(d[57]),"+f"(d[58]),"+f"(d[59]),"+f"(d[60]),"+f"(d[61]),"+f"(d[62]),"+f"(d[63]),"+f"(d[64]),"+f"(d[65]),"+f"(d[66]),"+f"(d[67]),"+f"(d[68]),"+f"(d[69]),"+f"(d[70]),"+f"(d[71]),"+f"(d[72]),"+f"(d[73]),"+f"(d[74]),"+f"(d[75]),"+f"(d[76]),"+f"(d[77]),"+f"(d[78]),"+f"(d[79]),"+f"(d[80]),"+f"(d[81]),"+f"(d[82]),"+f"(d[83]),"+f"(d[84]),"+f"(d[85]),"+f"(d[86]),"+f"(d[87]) : "l"(da), "l"(db), "r"(sd), "n"(TA), "n"(TB));
}
template<int TB> __device__ __forceinline__ void wgmma_rs_n8(float* d, uint32_t a0, uint32_t a1, uint32_t a2, uint32_t a3, uint64_t db, int sd){
  asm volatile("{ .reg .pred p; setp.ne.b32 p, %9, 0; wgmma.mma_async.sync.aligned.m64n8k16.f32.bf16.bf16 {%0,%1,%2,%3}, {%4,%5,%6,%7}, %8, p, 1, 1, %10; }"
   : "+f"(d[0]),"+f"(d[1]),"+f"(d[2]),"+f"(d[3]) : "r"(a0),"r"(a1),"r"(a2),"r"(a3), "l"(db), "r"(sd), "n"(TB));
}
template<int TB> __device__ __forceinline__ void wgmma_rs_n16(float* d, uint32_t a0, uint32_t a1, uint32_t a2, uint32_t a3, uint64_t db, int sd){
  asm volatile("{ .reg .pred p; setp.ne.b32 p, %13, 0; wgmma.mma_async.sync.aligned.m64n16k16.f32.bf16.bf16 {%0,%1,%2,%3,%4,%5,%6,%7}, {%8,%9,%10,%11}, %12, p, 1, 1, %14; }"
   : "+f"(d[0]),"+f"(d[1]),"+f"(d[2]),"+f"(d[3]),"+f"(d[4]),"+f"(d[5]),"+f"(d[6]),"+f"(d[7]) : "r"(a0),"r"(a1),"r"(a2),"r"(a3), "l"(db), "r"(sd), "n"(TB));
}
template<int TB> __device__ __forceinline__ void wgmma_rs_n24(float* d, uint32_t a0, uint32_t a1, uint32_t a2, uint32_t a3, uint64_t db, int sd){
  asm volatile("{ .reg .pred p; setp.ne.b32 p, %17, 0; wgmma.mma_async.sync.aligned.m64n24k16.f32.bf16.bf16 {%0,%1,%2,%3,%4,%5,%6,%7,%8,%9,%10,%11}, {%12,%13,%14,%15}, %16, p, 1, 1, %18; }"
   : "+f"(d[0]),"+f"(d[1]),"+f"(d[2]),"+f"(d[3]),"+f"(d[4]),"+f"(d[5]),"+f"(d[6]),"+f"(d[7]),"+f"(d[8]),"+f"(d[9]),"+f"(d[10]),"+f"(d[11]) : "r"(a0),"r"(a1),"r"(a2),"r"(a3), "l"(db), "r"(sd), "n"(TB));
}
template<int TB> __device__ __forceinline__ void wgmma_rs_n32(float* d, uint32_t a0, uint32_t a1, uint32_t a2, uint32_t a3, uint64_t db, int sd){
  asm volatile("{ .reg .pred p; setp.ne.b32 p, %21, 0; wgmma.mma_async.sync.aligned.m64n32k16.f32.bf16.bf16 {%0,%1,%2,%3,%4,%5,%6,%7,%8,%9,%10,%11,%12,%13,%14,%15}, {%16,%17,%18,%19}, %20, p, 1, 1, %22; }"
   : "+f"(d[0]),"+f"(d[1]),"+f"(d[2]),"+f"(d[3]),"+f"(d[4]),"+f"(d[5]),"+f"(d[6]),"+f"(d[7]),"+f"(d[8]),"+f"(d[9]),"+f"(d[10]),"+f"(d[11]),"+f"(d[12]),"+f"(d[13]),"+f"(d[14]),"+f"(d[15]) : "r"(a0),"r"(a1),"r"(a2),"r"(a3), "l"(db), "r"(sd), "n"(TB));
}
template<int TB> __device__ __forceinline__ void wgmma_rs_n40(float* d, uint32_t a0, uint32_t a1, uint32_t a2, uint32_t a3, uint64_t db, int sd){
  asm volatile("{ .reg .pred p; setp.ne.b32 p, %25, 0; wgmma.mma_async.sync.aligned.m64n40k16.f32.bf16.bf16 {%0,%1,%2,%3,%4,%5,%6,%7,%8,%9,%10,%11,%12,%13,%14,%15,%16,%17,%18,%19}, {%20,%21,%22,%23}, %24, p, 1, 1, %26; }"
   : "+f"(d[0]),"+f"(d[1]),"+f"(d[2]),"+f"(d[3]),"+f"(d[4]),"+f"(d[5]),"+f"(d[6]),"+f"(d[7]),"+f"(d[8]),"+f"(d[9]),"+f"(d[10]),"+f"(d[11]),"+f"(d[12]),"+f"(d[13]),"+f"(d[14]),"+f"(d[15]),"+f"(d[16]),"+f"(d[17]),"+f"(d[18]),"+f"(d[19]) : "r"(a0),"r"(a1),"r"(a2),"r"(a3), "l"(db), "r"(sd), "n"(TB));
}
template<int TB> __device__ __forceinline__ void wgmma_rs_n48(float* d, uint32_t a0, uint32_t a1, uint32_t a2, uint32_t a3, uint64_t db, int sd){
  asm volatile("{ .reg .pred p; setp.ne.b32 p, %29, 0; wgmma.mma_async.sync.aligned.m64n48k16.f32.bf16.bf16 {%0,%1,%2,%3,%4,%5,%6,%7,%8,%9,%10,%11,%12,%13,%14,%15,%16,%17,%18,%19,%20,%21,%22,%23}, {%24,%25,%26,%27}, %28, p, 1, 1, %30; }"
   : "+f"(d[0]),"+f"(d[1]),"+f"(d[2]),"+f"(d[3]),"+f"(d[4]),"+f"(d[5]),"+f"(d[6]),"+f"(d[7]),"+f"(d[8]),"+f"(d[9]),"+f"(d[10]),"+f"(d[11]),"+f"(d[12]),"+f"(d[13]),"+f"(d[14]),"+f"(d[15]),"+f"(d[16]),"+f"(d[17]),"+f"(d[18]),"+f"(d[19]),"+f"(d[20]),"+f"(d[21]),"+f"(d[22]),"+f"(d[23]) : "r"(a0),"r"(a1),"r"(a2),"r"(a3), "l"(db), "r"(sd), "n"(TB));
}
template<int TB> __device__ __forceinline__ void wgmma_rs_n56(float* d, uint32_t a0, uint32_t a1, uint32_t a2, uint32_t a3, uint64_t db, int sd){
  asm volatile("{ .reg .pred p; setp.ne.b32 p, %33, 0; wgmma.mma_async.sync.aligned.m64n56k16.f32.bf16.bf16 {%0,%1,%2,%3,%4,%5,%6,%7,%8,%9,%10,%11,%12,%13,%14,%15,%16,%17,%18,%19,%20,%21,%22,%23,%24,%25,%26,%27}, {%28,%29,%30,%31}, %32, p, 1, 1, %34; }"
   : "+f"(d[0]),"+f"(d[1]),"+f"(d[2]),"+f"(d[3]),"+f"(d[4]),"+f"(d[5]),"+f"(d[6]),"+f"(d[7]),"+f"(d[8]),"+f"(d[9]),"+f"(d[10]),"+f"(d[11]),"+f"(d[12]),"+f"(d[13]),"+f"(d[14]),"+f"(d[15]),"+f"(d[16]),"+f"(d[17]),"+f"(d[18]),"+f"(d[19]),"+f"(d[20]),"+f"(d[21]),"+f"(d[22]),"+f"(d[23]),"+f"(d[24]),"+f"(d[25]),"+f"(d[26]),"+f"(d[27]) : "r"(a0),"r"(a1),"r"(a2),"r"(a3), "l"(db), "r"(sd), "n"(TB));
}
template<int TB> __device__ __forceinline__ void wgmma_rs_n64(float* d, uint32_t a0, uint32_t a1, uint32_t a2, uint32_t a3, uint64_t db, int sd){
  asm volatile("{ .reg .pred p; setp.ne.b32 p, %37, 0; wgmma.mma_async.sync.aligned.m64n64k16.f32.bf16.bf16 {%0,%1,%2,%3,%4,%5,%6,%7,%8,%9,%10,%11,%12,%13,%14,%15,%16,%17,%18,%19,%20,%21,%22,%23,%24,%25,%26,%27,%28,%29,%30,%31}, {%32,%33,%34,%35}, %36, p, 1, 1, %38; }"
   : "+f"(d[0]),"+f"(d[1]),"+f"(d[2]),"+f"(d[3]),"+f"(d[4]),"+f"(d[5]),"+f"(d[6]),"+f"(d[7]),"+f"(d[8]),"+f"(d[9]),"+f"(d[10]),"+f"(d[11]),"+f"(d[12]),"+f"(d[13]),"+f"(d[14]),"+f"(d[15]),"+f"(d[16]),"+f"(d[17]),"+f"(d[18]),"+f"(d[19]),"+f"(d[20]),"+f"(d[21]),"+f"(d[22]),"+f"(d[23]),"+f"(d[24]),"+f"(d[25]),"+f"(d[26]),"+f"(d[27]),"+f"(d[28]),"+f"(d[29]),"+f"(d[30]),"+f"(d[31]) : "r"(a0),"r"(a1),"r"(a2),"r"(a3), "l"(db), "r"(sd), "n"(TB));
}
template<int N,int TA,int TB> __device__ __forceinline__ void wgmma_ss(float* d, uint64_t da, uint64_t db, int sd){
  if constexpr(N==176) wgmma_ss_n176<TA,TB>(d,da,db,sd);
}
template<int N,int TB> __device__ __forceinline__ void wgmma_rs(float* d, uint32_t a0,uint32_t a1,uint32_t a2,uint32_t a3, uint64_t db, int sd){
  if constexpr(N==8) wgmma_rs_n8<TB>(d,a0,a1,a2,a3,db,sd);
  if constexpr(N==16) wgmma_rs_n16<TB>(d,a0,a1,a2,a3,db,sd);
  if constexpr(N==24) wgmma_rs_n24<TB>(d,a0,a1,a2,a3,db,sd);
  if constexpr(N==32) wgmma_rs_n32<TB>(d,a0,a1,a2,a3,db,sd);
  if constexpr(N==40) wgmma_rs_n40<TB>(d,a0,a1,a2,a3,db,sd);
  if constexpr(N==48) wgmma_rs_n48<TB>(d,a0,a1,a2,a3,db,sd);
  if constexpr(N==56) wgmma_rs_n56<TB>(d,a0,a1,a2,a3,db,sd);
  if constexpr(N==64) wgmma_rs_n64<TB>(d,a0,a1,a2,a3,db,sd);
}

typedef __nv_bfloat16 bf16;
constexpr int S_ = 2048, D_ = 512, F_ = 1376, FS = 176;

__device__ __forceinline__ uint32_t smem_u32(const void* p){ return (uint32_t)__cvta_generic_to_shared(p); }
__device__ __forceinline__ void mbar_init(uint32_t bar, uint32_t cnt){ asm volatile("mbarrier.init.shared::cta.b64 [%0], %1;"::"r"(bar),"r"(cnt):"memory"); }
__device__ __forceinline__ void mbar_expect_tx(uint32_t bar, uint32_t bytes){ asm volatile("mbarrier.arrive.expect_tx.shared::cta.b64 _, [%0], %1;"::"r"(bar),"r"(bytes):"memory"); }
__device__ __forceinline__ void mbar_arrive(uint32_t bar){ asm volatile("mbarrier.arrive.shared::cta.b64 _, [%0];"::"r"(bar):"memory"); }
__device__ __forceinline__ void mbar_arrive_cl(uint32_t cbar){ asm volatile("mbarrier.arrive.shared::cluster.b64 _, [%0];"::"r"(cbar):"memory"); }
__device__ __forceinline__ uint32_t mapa(uint32_t a, uint32_t cta){ uint32_t r; asm volatile("mapa.shared::cluster.u32 %0, %1, %2;":"=r"(r):"r"(a),"r"(cta)); return r; }
__device__ __forceinline__ void mbar_wait(uint32_t bar, uint32_t ph){
  asm volatile("{ .reg .pred p; .reg .u32 c; mov.u32 c, 0;\n"
               "WL: mbarrier.try_wait.parity.shared::cta.b64 p, [%0], %1; @p bra WD; add.u32 c,c,1; setp.lt.u32 p, c, 2000000; @p bra WL; trap;\n"
               "WD: }"::"r"(bar),"r"(ph):"memory"); }
__device__ __forceinline__ bool elect_one(){ uint32_t p; asm volatile("{ .reg .pred P; elect.sync _|P, 0xffffffff; selp.u32 %0,1,0,P; }":"=r"(p)); return p; }
__device__ __forceinline__ void tma2d(uint32_t dst, const CUtensorMap* m, int c0, int c1, uint32_t bar){
  asm volatile("cp.async.bulk.tensor.2d.shared::cluster.global.mbarrier::complete_tx::bytes [%0], [%1, {%3, %4}], [%2];"::"r"(dst),"l"(m),"r"(bar),"r"(c0),"r"(c1):"memory"); }
__device__ __forceinline__ void tma2d_mc(uint32_t dst, const CUtensorMap* m, int c0, int c1, uint32_t bar){
  asm volatile("cp.async.bulk.tensor.2d.shared::cluster.global.mbarrier::complete_tx::bytes.multicast::cluster [%0], [%1, {%3, %4}], [%2], %5;"::"r"(dst),"l"(m),"r"(bar),"r"(c0),"r"(c1),"h"((uint16_t)3):"memory"); }
__device__ __forceinline__ void cluster_sync(){ asm volatile("barrier.cluster.arrive.release.aligned; barrier.cluster.wait.acquire.aligned;":::"memory"); }
__device__ __forceinline__ void wg_fence(){ asm volatile("wgmma.fence.sync.aligned;":::"memory"); }
__device__ __forceinline__ void wg_commit(){ asm volatile("wgmma.commit_group.sync.aligned;":::"memory"); }
template<int N> __device__ __forceinline__ void wg_wait(){ asm volatile("wgmma.wait_group.sync.aligned %0;"::"n"(N):"memory"); }
__device__ __forceinline__ uint64_t make_desc(uint32_t addr, uint32_t lbo, uint32_t sbo, uint32_t sw){ return (uint64_t)((addr&0x3FFFF)>>4) | ((uint64_t)((lbo&0x3FFFF)>>4)<<16) | ((uint64_t)((sbo&0x3FFFF)>>4)<<32) | ((uint64_t)sw<<62); }
__device__ __forceinline__ void ldsm4t(uint32_t a, uint32_t& r0, uint32_t& r1, uint32_t& r2, uint32_t& r3){ asm volatile("ldmatrix.sync.aligned.m8n8.x4.trans.shared.b16 {%0,%1,%2,%3}, [%4];":"=r"(r0),"=r"(r1),"=r"(r2),"=r"(r3):"r"(a):"memory"); }
__device__ __forceinline__ void stsm4(uint32_t a, uint32_t r0, uint32_t r1, uint32_t r2, uint32_t r3){ asm volatile("stmatrix.sync.aligned.m8n8.x4.shared.b16 [%0], {%1,%2,%3,%4};"::"r"(a),"r"(r0),"r"(r1),"r"(r2),"r"(r3):"memory"); }
__device__ __forceinline__ uint32_t pack_bf16(float lo, float hi){ uint32_t r; asm("cvt.rn.bf16x2.f32 %0, %1, %2;":"=r"(r):"f"(hi),"f"(lo)); return r; }
__device__ __forceinline__ float bf_lo(uint32_t v){ return __uint_as_float(v<<16); }
__device__ __forceinline__ float bf_hi(uint32_t v){ return __uint_as_float(v&0xffff0000u); }
__device__ __forceinline__ float rbf(float x){ return __bfloat162float(__float2bfloat16(x)); }
__device__ __forceinline__ uint32_t hadd2_bf16(uint32_t a, uint32_t b){ uint32_t r; asm("add.rn.bf16x2 %0, %1, %2;":"=r"(r):"r"(a),"r"(b)); return r; }
__device__ __forceinline__ float tanh_fast(float x){ float r; asm("tanh.approx.f32 %0, %1;":"=f"(r):"f"(x)); return r; }

__device__ __forceinline__ void st_rlx128(void* p, uint32_t a, uint32_t b, uint32_t c, uint32_t d){
  asm volatile("{ .reg .b64 l,h; .reg .b128 v; mov.b64 l,{%1,%2}; mov.b64 h,{%3,%4}; mov.b128 v,{l,h}; st.relaxed.gpu.global.b128 [%0], v; }"::"l"(p),"r"(a),"r"(b),"r"(c),"r"(d):"memory"); }
__device__ __forceinline__ void ld_rlx128(const void* p, uint4& v){
  asm volatile("{ .reg .b64 l,h; .reg .b128 v; ld.relaxed.gpu.global.b128 v, [%4]; mov.b128 {l,h}, v; mov.b64 {%0,%1}, l; mov.b64 {%2,%3}, h; }":"=r"(v.x),"=r"(v.y),"=r"(v.z),"=r"(v.w):"l"(p):"memory"); }
__device__ __forceinline__ void st_async128(uint32_t dst, uint32_t a, uint32_t b, uint32_t c, uint32_t d, uint32_t cbar){
  asm volatile("st.async.weak.shared::cluster.mbarrier::complete_tx::bytes.v4.b32 [%0], {%1,%2,%3,%4}, [%5];"::"r"(dst),"r"(a),"r"(b),"r"(c),"r"(d),"r"(cbar)); }
__device__ __forceinline__ void mbar_wait_nomem(uint32_t bar, uint32_t ph){
  asm volatile("{ .reg .pred p; .reg .u32 c; mov.u32 c, 0;\n"
               "WL: mbarrier.try_wait.parity.shared::cta.b64 p, [%0], %1; @p bra WD; add.u32 c,c,1; setp.lt.u32 p, c, 2000000; @p bra WL; trap;\n"
               "WD: }"::"r"(bar),"r"(ph)); }
__device__ __forceinline__ void bulk_g2s(uint32_t dst, const void* src, uint32_t bytes, uint32_t bar){
  asm volatile("cp.async.bulk.shared::cluster.global.mbarrier::complete_tx::bytes [%0], [%1], %2, [%3];"::"r"(dst),"l"(src),"r"(bytes),"r"(bar):"memory"); }
__device__ __forceinline__ void mbar_wait_cl(uint32_t bar, uint32_t ph){
  asm volatile("{ .reg .pred p; .reg .u32 c; mov.u32 c, 0;\n"
               "WL: mbarrier.try_wait.parity.acquire.cluster.shared::cta.b64 p, [%0], %1; @p bra WD; add.u32 c,c,1; setp.lt.u32 p, c, 2000000; @p bra WL; trap;\n"
               "WD: }"::"r"(bar),"r"(ph):"memory"); }
__device__ __forceinline__ void lds128(uint32_t a, uint32_t& x, uint32_t& y, uint32_t& z, uint32_t& w){ asm volatile("ld.shared.v4.u32 {%0,%1,%2,%3}, [%4];":"=r"(x),"=r"(y),"=r"(z),"=r"(w):"r"(a):"memory"); }
__device__ __forceinline__ void tma3d_red_add(const CUtensorMap* m, int c0, int c1, int c2, uint32_t src){
  asm volatile("cp.reduce.async.bulk.tensor.3d.global.shared::cta.add.tile.bulk_group [%0, {%1, %2, %3}], [%4];"::"l"(m),"r"(c0),"r"(c1),"r"(c2),"r"(src):"memory"); }
__device__ __forceinline__ void stsm4_nm(uint32_t a, uint32_t r0, uint32_t r1, uint32_t r2, uint32_t r3){ asm volatile("stmatrix.sync.aligned.m8n8.x4.shared.b16 [%0], {%1,%2,%3,%4};"::"r"(a),"r"(r0),"r"(r1),"r"(r2),"r"(r3)); }
__device__ __forceinline__ void tma3d(uint32_t dst, const CUtensorMap* m, int c0, int c1, int c2, uint32_t bar){
  asm volatile("cp.async.bulk.tensor.3d.shared::cluster.global.mbarrier::complete_tx::bytes [%0], [%1, {%3, %4, %5}], [%2];"::"r"(dst),"l"(m),"r"(bar),"r"(c0),"r"(c1),"r"(c2):"memory"); }
__device__ __forceinline__ uint32_t lds32(uint32_t a){ uint32_t v; asm volatile("ld.shared.u32 %0, [%1];":"=r"(v):"r"(a)); return v; }
__device__ __forceinline__ void sts128(uint32_t a, uint32_t x, uint32_t y, uint32_t z, uint32_t w){ asm volatile("st.shared.v4.u32 [%0], {%1,%2,%3,%4};"::"r"(a),"r"(x),"r"(y),"r"(z),"r"(w):"memory"); }
__device__ __forceinline__ uint4 ldg_nc128(const void* p){ uint4 v; asm volatile("ld.global.nc.L1::no_allocate.v4.u32 {%0,%1,%2,%3}, [%4];":"=r"(v.x),"=r"(v.y),"=r"(v.z),"=r"(v.w):"l"(p)); return v; }
__device__ __forceinline__ uint32_t hmul2_bf16(uint32_t a, uint32_t b){ uint32_t r; asm("mul.rn.bf16x2 %0, %1, %2;":"=r"(r):"r"(a),"r"(b)); return r; }
__device__ __forceinline__ uint32_t hsub2_bf16(uint32_t a, uint32_t b){ uint32_t r; asm("sub.rn.bf16x2 %0, %1, %2;":"=r"(r):"r"(a),"r"(b)); return r; }
__device__ __forceinline__ void poll_ge(const unsigned* p, unsigned target){
  unsigned v; int n=0;
  do{ asm volatile("ld.acquire.gpu.global.u32 %0, [%1];":"=r"(v):"l"(p):"memory"); if(++n>2000000) __trap(); }while((int)(v-target)<0); }
__device__ __forceinline__ void signal_add(unsigned* p){ asm volatile("fence.acq_rel.gpu;":::"memory"); asm volatile("red.relaxed.gpu.global.add.u32 [%0], 1;"::"l"(p):"memory"); }
__host__ __device__ __forceinline__ int pos2row(int pos){
  int P = 1 - (pos >> 10), r = pos & 1023, thr = r >> 3, ii = r & 7;
  int w = thr >> 5, lane = thr & 31, g = lane >> 2, t = lane & 3, c = g >> 1, p = g & 1;
  int qp = 64*P + 8*ii + 2*((t - c) & 3) + (c & 1);
  return 16*(127 - qp) + 8*(c >> 1) + 2*w + p;
}

__device__ __align__(1024) bf16 g_hT[D_*S_];
__device__ __align__(1024) uint4 g_xa[128*2*128*8];
__device__ uint4 g_stat[16*2*8*32];
__device__ uint4 g_csp[8*16*88];
__device__ unsigned g_iflag[16*2*2*4];
__device__ unsigned g_cnt[4*32];
#define STAMP(i)

#define NIN 5
#define LEAD 2
constexpr uint32_t G2_CH = 0x33221010u, G2_PEER = 0xAC;
constexpr int NS = 6, WSLOT = 24576, NX = 4, XSLOT = 8192;
constexpr int OFF_RES0 = 0, OFF_X = 8192, OFF_RES1 = 73728, OFF_W = 81920;
constexpr int OFF_CS = OFF_W + NS*WSLOT, OFF_ROW = OFF_CS + 2*FS*4, OFF_BAR = OFF_ROW + 1024;
constexpr int TBL = 8320, UPL = 2112, UCH = 2*UPL, QP = 1088, KVCH = 4224;
constexpr int OFF_TBL = 32768, OFF_U = OFF_TBL + 4*TBL, OFF_XAL = 83968, OFF_XAE = OFF_W + 1*WSLOT;
constexpr int OFF_KV = OFF_W + 2*WSLOT, OFF_Q = OFF_W + 4*WSLOT, OFF_CST = OFF_X;
static_assert(OFF_U + 4*UCH <= OFF_XAL && OFF_XAL + 16384 <= OFF_W + WSLOT, "overlay");
constexpr int B_WFULL = 0, B_WEMPTY = B_WFULL+NS, B_XFULL = B_WEMPTY+NS, B_XEMPTY = B_XFULL+2*NX, B_PRDY = B_XEMPTY+2*NX, B_AFULL = B_PRDY+2,
              B_RES = B_AFULL+2, B_PAR = B_RES+2, B_CSW = B_PAR+2, B_INIT = B_CSW+1, B_KV = B_INIT+2, B_U = B_KV+8, B_XA = B_U+8, B_HD = B_XA+2, NBAR = B_HD+2;
constexpr int SMEM_BYTES = OFF_BAR + NBAR*8;
static_assert(SMEM_BYTES<=232448,"smem");

struct Maps { CUtensorMap k, v, wg64, wg48, wu64, wu48, wd, ht, out; };

__device__ __forceinline__ void load_w_stage(const Maps& maps, uint32_t dst, int col, int k0, uint32_t fb){
  tma2d(dst,            &maps.wg64, col,     k0, fb);
  tma2d(dst+4096,       &maps.wg64, col+64,  k0, fb);
  tma2d(dst+8192,       &maps.wg48, col+128, k0, fb);
  tma2d(dst+12288,      &maps.wu64, col,     k0, fb);
  tma2d(dst+12288+4096, &maps.wu64, col+64,  k0, fb);
  tma2d(dst+12288+8192, &maps.wu48, col+128, k0, fb);
}

template<int N> __device__ __forceinline__ void conv_mma(float* acc, const uint32_t* R, uint64_t db){
  wgmma_rs<N,0>(acc, R[0],R[1],R[1],R[2], db,   1);
  wgmma_rs<N,0>(acc, R[2],R[3],R[3],R[4], db+1, 1);
}
__device__ __forceinline__ void conv_lda(uint32_t* R, const uint32_t* tb, int off){
  #pragma unroll
  for(int s=0;s<5;s++) R[s]=lds32(tb[s]+off);
}
__device__ __forceinline__ void conv_epi(const float* acc, float n0, float n1, float n2, float n3, int lane, uint32_t xa_addr, int chl, bf16* dst){
  const int t=lane&3, c=lane>>3;
  const bool sh = t<c, odd = c&1, hi = c>>1;
  const int src1 = ((lane^8)&~3) | ((t + (odd? 3:1))&3);
  uint4 xv, av;
  lds128(xa_addr+((chl^(lane&7))<<4), xv.x,xv.y,xv.z,xv.w);
  lds128(xa_addr+(((4+chl)^(lane&7))<<4), av.x,av.y,av.z,av.w);
  float z[8];
  #pragma unroll
  for(int ii=0;ii<8;ii++){
    const float nx[4]={n0,n1,n2,n3};
    float v[4];
    #pragma unroll
    for(int q=0;q<4;q++) v[q] = sh ? (ii<7? acc[4*ii+4+q] : nx[q]) : acc[4*ii+q];
    const float r0 = (odd? v[1]:v[0]) + __shfl_sync(~0u, odd? v[0]:v[1], src1);
    const float r1 = (odd? v[3]:v[2]) + __shfl_sync(~0u, odd? v[2]:v[3], src1);
    z[ii] = (hi? r1:r0) + __shfl_xor_sync(~0u, hi? r0:r1, 18);
  }
  uint4 o;
  o.x=hadd2_bf16(xv.x,hmul2_bf16(av.x,pack_bf16(z[0],z[1]))); o.y=hadd2_bf16(xv.y,hmul2_bf16(av.y,pack_bf16(z[2],z[3])));
  o.z=hadd2_bf16(xv.z,hmul2_bf16(av.z,pack_bf16(z[4],z[5]))); o.w=hadd2_bf16(xv.w,hmul2_bf16(av.w,pack_bf16(z[6],z[7])));
  *(uint4*)dst = o;
}

__global__ void __cluster_dims__(2,1,1) __launch_bounds__(384,1)
fused_kernel(const __grid_constant__ Maps maps, const bf16* __restrict__ q, const bf16* __restrict__ shk, const bf16* __restrict__ ssmk,
             const bf16* __restrict__ ssmD, bf16* __restrict__ out){
  extern __shared__ __align__(1024) uint8_t smem_raw[];
  const uint32_t sb = smem_u32(smem_raw);
  const int tid = threadIdx.x, lane = tid&31;
  const int warp = __shfl_sync(0xffffffffu, tid>>5, 0);
  const int wg = warp>>2;
  const int b = blockIdx.x, rank = b&1;
  const int f = b&7, rt = b>>3, fp = f>>1;
  const uint32_t bar = sb+OFF_BAR;

  if(wg==2){
    asm volatile("setmaxnreg.dec.sync.aligned.u32 56;");
    if(warp==8){
      if(elect_one()){
        #pragma unroll
        for(int i=0;i<8;i++) mbar_init(bar+8*(B_KV+i),1);
        asm volatile("fence.proxy.async.shared::cta;":::"memory");
        #pragma unroll
        for(int i=0;i<8;i++){
          const uint32_t fb=bar+8*(B_KV+i);
          mbar_expect_tx(fb, 2176+2048);
          tma3d(sb+OFF_KV+i*KVCH,      &maps.k, (b>>1)*8, i*32+rank*16-1, 0, fb);
          tma3d(sb+OFF_KV+i*KVCH+2176, &maps.v, (b>>1)*8, i*32+rank*16,   0, fb);
        }
      }
      __syncwarp();
    } else if(warp==9){
      if(lane==0){
        for(int i=0;i<NS;i++){ mbar_init(bar+8*(B_WFULL+i),1); mbar_init(bar+8*(B_WEMPTY+i),8); }
        for(int i=0;i<2*NX;i++){ mbar_init(bar+8*(B_XFULL+i),1); mbar_init(bar+8*(B_XEMPTY+i),8); }
        for(int i=0;i<2;i++){ mbar_init(bar+8*(B_PRDY+i),4); mbar_init(bar+8*(B_AFULL+i),1); mbar_init(bar+8*(B_RES+i),1); mbar_expect_tx(bar+8*(B_AFULL+i), 22528);
          mbar_init(bar+8*(B_PAR+i),2); mbar_init(bar+8*(B_INIT+i),1); mbar_init(bar+8*(B_XA+i),1); }
        mbar_init(bar+8*B_HD,10); mbar_init(bar+8*(B_HD+1),8);
        mbar_init(bar+8*B_CSW,1);
        for(int i=0;i<8;i++){ mbar_init(bar+8*(B_U+i),1); mbar_expect_tx(bar+8*(B_U+i), 2048); }
        asm volatile("fence.mbarrier_init.release.cluster;":::"memory");
      }
      __syncwarp();
    }
    const unsigned epoch = *(volatile unsigned*)&g_cnt[96] + 1;
    const uint32_t par = epoch&1;
    const int cp = lane&3;
    uint32_t sw[4];
    { const uint4 w = *(const uint4*)(shk + ((b>>1)*8+cp*2)*4);
      sw[0]=__byte_perm(w.x,w.z,0x5410); sw[1]=__byte_perm(w.x,w.z,0x7632); sw[2]=__byte_perm(w.y,w.w,0x5410); sw[3]=__byte_perm(w.y,w.w,0x7632); }
    asm volatile("barrier.cluster.arrive.relaxed.aligned;":::"memory");
    asm volatile("barrier.cluster.wait.aligned;":::"memory");
    asm volatile("bar.sync 4, 128;":::"memory");
    {
      const int gl = (warp&1)*8 + (lane>>2);
      const uint32_t udst = mapa(sb+OFF_U+(cp&1)*2*UCH, cp>>1), ubar = mapa(bar+8*B_U, cp>>1);
      #pragma unroll 1
      for(int T=(warp>>1)&1; T<8; T+=2){
        mbar_wait(bar+8*(B_KV+T), 0);
        if(T==0) STAMP(64); if(T==7) STAMP(65);
        const uint32_t ka = sb+OFF_KV+T*KVCH+gl*16+cp*4, va = ka+2176;
        uint32_t k0=lds32(ka+5*272), k1=lds32(ka+6*272), k2=lds32(ka+7*272), u[8];
        #pragma unroll
        for(int r=0;r<8;r++){
          const uint32_t k3=lds32(ka+16+r*272), vv=lds32(va+r*256);
          uint32_t a=hmul2_bf16(k0,sw[3]); a=hadd2_bf16(a,hmul2_bf16(k1,sw[2])); a=hadd2_bf16(a,hmul2_bf16(k2,sw[1])); a=hadd2_bf16(a,hmul2_bf16(k3,sw[0]));
          u[r]=hmul2_bf16(a,vv); k0=k1; k1=k2; k2=k3;
        }
        const int R = 255-(T*32+rank*16+gl);
        const uint32_t d = udst + (R&1)*UPL + (R>>1)*16;
        st_async128(d,     __byte_perm(u[7],u[6],0x5410), __byte_perm(u[5],u[4],0x5410), __byte_perm(u[3],u[2],0x5410), __byte_perm(u[1],u[0],0x5410), ubar+8*T);
        st_async128(d+UCH, __byte_perm(u[7],u[6],0x7632), __byte_perm(u[5],u[4],0x7632), __byte_perm(u[3],u[2],0x7632), __byte_perm(u[1],u[0],0x7632), ubar+8*T);
        if(warp==9 && T==2){
          if(lane==0) poll_ge(&g_cnt[0], epoch*128);
          __syncwarp();
          if(elect_one()){
            asm volatile("fence.proxy.async.global;":::"memory");
            mbar_expect_tx(bar+8*(B_XA+1), 16384); bulk_g2s(sb+OFF_XAE, &g_xa[(b*2+1)*1024], 16384, bar+8*(B_XA+1));
            mbar_expect_tx(bar+8*B_XA, 16384);     bulk_g2s(sb+OFF_XAL, &g_xa[(b*2)*1024],   16384, bar+8*B_XA);
          }
          __syncwarp();
          STAMP(66);
        }
        if(warp==8 && T==0){
          if(elect_one()){ mbar_expect_tx(bar+8*B_CSW, 22528); load_w_stage(maps, sb+OFF_CST, f*FS, rt*32, bar+8*B_CSW); }
          __syncwarp();
        }
      }
    }
    if(warp==8){
      int slot=0, ph=0;
      #pragma unroll 1
      for(int it=0; it<24; it++){
        mbar_wait(bar+8*(B_WEMPTY+slot), ph);
        if(elect_one()){
          const uint32_t fb = bar+8*(B_WFULL+slot), dst = sb+OFF_W+(5-slot)*WSLOT;
          mbar_expect_tx(fb, 22528);
          if(it<16) load_w_stage(maps, dst, f*FS, it*32, fb);
          else {
            const int j = it-16, ci = (G2_CH >> (4*j)) & 3, kh = ((G2_PEER >> j) & 1) ^ rank;
            tma2d(dst, &maps.wd, rank*256+((fp+ci)&3)*64, (2*fp+kh)*FS, fb);
          }
        }
        __syncwarp();
        if(++slot==NS){ slot=0; ph^=1; }
      }
    } else if(warp==9){
      auto ldx=[&](int w, int it){
        if(elect_one()){
          const uint32_t fb = bar+8*(B_XFULL+w*NX+(it&3));
          mbar_expect_tx(fb, XSLOT);
          tma2d_mc(sb+OFF_X+(w*NX+(it&3))*XSLOT+rank*4096, &maps.ht, w*1024+rt*64, it*64+rank*32, fb);
        }
        __syncwarp();
      };
      #pragma unroll
      for(int w=0;w<2;w++){
        mbar_wait(bar+8*(B_HD+w), 0);
        STAMP(67+w*3);
        if(lane==0){ signal_add(&g_cnt[32+32*w]); STAMP(68+w*3); poll_ge(&g_cnt[32+32*w], epoch*128); asm volatile("fence.proxy.async.global;":::"memory"); }
        __syncwarp();
        STAMP(69+w*3);
        ldx(w,0);
        if(elect_one()){
          const uint32_t fb = bar+8*(B_RES+w), dst = sb+(w? OFF_RES1:OFF_RES0);
          mbar_expect_tx(fb, XSLOT);
          tma2d(dst,      &maps.ht, w*1024+rt*64, rank*256+fp*64,    fb);
          tma2d(dst+4096, &maps.ht, w*1024+rt*64, rank*256+fp*64+32, fb);
        }
        __syncwarp();
        ldx(w,1); ldx(w,2);
      }
      if(b==0 && lane==0) *(volatile unsigned*)&g_cnt[96] = epoch;
      ldx(0,3); ldx(1,3);
      #pragma unroll 1
      for(int it=4; it<8; it++){
        #pragma unroll
        for(int w=0;w<2;w++){ mbar_wait(bar+8*(B_XEMPTY+w*NX+(it&3)), 0); ldx(w,it); }
      }
    } else {
      const int w = warp-10;
      mbar_wait(bar+8*B_CSW, 0);
      {
        const uint32_t base = sb+OFF_CST+w*12288;
        float c[6];
        #pragma unroll
        for(int i=0;i<6;i++) c[i]=0.f;
        #pragma unroll 4
        for(int k=0;k<32;k++){
          const uint32_t ad = base + k*128 + ((((lane>>2)^(k&7))<<4)|((lane&3)<<2));
          #pragma unroll
          for(int i=0;i<3;i++){ const uint32_t v=lds32(ad+i*4096); c[2*i]+=bf_lo(v); c[2*i+1]+=bf_hi(v); }
        }
        #pragma unroll
        for(int i=0;i<3;i++){
          const float o0=__shfl_down_sync(~0u,c[2*i],1), o1=__shfl_down_sync(~0u,c[2*i+1],1);
          const int j = i*16+(lane>>1);
          if(!(lane&1) && j<44) st_rlx128(&g_csp[(f*16+rt)*88+w*44+j], (__float_as_uint(c[2*i])&~1u)|par, __float_as_uint(c[2*i+1]), __float_as_uint(o0), __float_as_uint(o1));
        }
        __syncwarp();
        if(lane==0) mbar_arrive(bar+8*B_HD);
        STAMP(73+w);
      }
      const uint32_t rbase = sb+(w? OFF_RES1:OFF_RES0);
      mbar_wait(bar+8*(B_RES+w), 0);
      {
        float s0=0.f,s1=0.f,q0=0.f,q1=0.f;
        #pragma unroll 8
        for(int k=0;k<64;k++){
          const uint32_t v=lds32(rbase + k*128 + ((((lane>>2)^(k&7))<<4)|((lane&3)<<2)));
          const float a=bf_lo(v), bb=bf_hi(v); s0+=a; q0=fmaf(a,a,q0); s1+=bb; q1=fmaf(bb,bb,q1);
        }
        st_rlx128(&g_stat[((rt*2+w)*8+f)*32+lane], (__float_as_uint(s0)&~1u)|par, __float_as_uint(q0), __float_as_uint(s1), __float_as_uint(q1));
      }
      {
        float* cs=(float*)(smem_raw+OFF_CS);
        #pragma unroll 1
        for(int j=lane;j<44;j+=32){
          float c0=0.f,c1=0.f,c2=0.f,c3=0.f;
          #pragma unroll 1
          for(int kb=0;kb<16;kb+=8){
            uint4 v[8]; int n=0; uint32_t bad;
            do{
              bad=0;
              #pragma unroll
              for(int u=0;u<8;u++) ld_rlx128(&g_csp[(f*16+kb+u)*88+w*44+j], v[u]);
              #pragma unroll
              for(int u=0;u<8;u++) bad|=v[u].x^par;
              if(++n>1000000) __trap();
            }while(bad&1);
            #pragma unroll
            for(int u=0;u<8;u++){ c0+=__uint_as_float(v[u].x); c1+=__uint_as_float(v[u].y); c2+=__uint_as_float(v[u].z); c3+=__uint_as_float(v[u].w); }
          }
          *(float2*)(cs+8*j+2*w)=make_float2(c0,c1); *(float2*)(cs+8*j+4+2*w)=make_float2(c2,c3);
        }
        __syncwarp();
        if(lane==0) mbar_arrive(bar+8*(B_PAR+(w^1)));
      }
      {
        float s0=0.f,s1=0.f,q0=0.f,q1=0.f;
        uint4 v[8]; int n=0; uint32_t bad;
        do{
          bad=0;
          #pragma unroll
          for(int u=0;u<8;u++) ld_rlx128(&g_stat[((rt*2+w)*8+u)*32+lane], v[u]);
          #pragma unroll
          for(int u=0;u<8;u++) bad|=v[u].x^par;
          if(++n>1000000) __trap();
        }while(bad&1);
        #pragma unroll
        for(int u=0;u<8;u++){ s0+=__uint_as_float(v[u].x); q0+=__uint_as_float(v[u].y); s1+=__uint_as_float(v[u].z); q1+=__uint_as_float(v[u].w); }
        const float m0=s0*(1.f/512), m1=s1*(1.f/512);
        const float v0=fmaxf(q0*(1.f/512)-m0*m0,0.f), v1=fmaxf(q1*(1.f/512)-m1*m1,0.f);
        const float r0=1.f/rbf(sqrtf(rbf(rbf(v0)+1e-5f))), r1=1.f/rbf(sqrtf(rbf(rbf(v1)+1e-5f)));
        *(float4*)(smem_raw+OFF_ROW+w*512+lane*16)=make_float4(-rbf(m0),r0,-rbf(m1),r1);
        __syncwarp();
        if(lane==0) mbar_arrive(bar+8*(B_PAR+w));
        STAMP(75+w);
      }
      {
        const int lch = 8*((lane&7)>>1) + 2*(lane>>3) + (lane&1);
        #pragma unroll 2
        for(int m8=0;m8<8;m8++){
          const int row = pos2row(w*1024+rt*64+m8*8+(lane>>2));
          uint4* o = (uint4*)(out+row*512+rank*256+fp*64)+(lane&3);
          #pragma unroll
          for(int hh=0;hh<2;hh++){
            uint4 v; ldsm4t(rbase+(hh*32+lch)*128+((m8^(lch&7))<<4), v.x,v.y,v.z,v.w);
            o[hh*4]=v;
          }
        }
        asm volatile("fence.proxy.async.global;":::"memory");
        asm volatile("fence.acq_rel.gpu;":::"memory");
        __syncwarp();
        if(lane==0) asm volatile("st.relaxed.gpu.global.u32 [%0], %1;"::"l"(&g_iflag[((rt*2+rank)*2+w)*4+fp]),"r"(epoch):"memory");
        if(lane<4){ unsigned v; int n=0; do{ asm volatile("ld.acquire.gpu.global.u32 %0, [%1];":"=r"(v):"l"(&g_iflag[((rt*2+rank)*2+w)*4+lane]):"memory"); if(++n>1000000) __trap(); }while(v!=epoch); }
        __syncwarp();
        if(lane==0) mbar_arrive(bar+8*(B_INIT+w));
        STAMP(77+w);
      }
    }
  } else {
    uint4 kq[4]; uint32_t kn[4]; uint4 xq[4];
    #pragma unroll
    for(int i=0;i<4;i++){ const bf16* p = ssmk + (b*4+i)*2048 + tid*8; kq[i]=ldg_nc128(p); kn[i] = tid<255 ? *(const uint32_t*)(p+8) : 0u; }
    const int qrow = pos2row(((warp>>2)^1)*1024 + b*8 + (warp&3)*2);
    #pragma unroll
    for(int i=0;i<4;i++) xq[i]=ldg_nc128(q + (qrow-(i>>1)*128)*512 + (i&1)*256 + lane*8);
    const uint32_t dbits = *(const uint32_t*)(ssmD + b*4 + wg*2);
    asm volatile("setmaxnreg.inc.sync.aligned.u32 224;");
    asm volatile("barrier.cluster.arrive.relaxed.aligned;":::"memory");
    const int wq = warp&3, g = lane>>2, t = lane&3;
    if(tid<8){ sts128(sb+OFF_U+tid*UPL+128*16, 0,0,0,0); }
    if(tid<12){ sts128(sb+OFF_TBL+(tid&3)*TBL+(tid>>2)*16, 0,0,0,0); }
    {
      const int Q = tid+2;
      const uint32_t ta = sb+OFF_TBL+((Q*32)^(((Q>>2)&3)<<5));
      #pragma unroll
      for(int i=0;i<4;i++){
        sts128(ta+i*TBL, kq[i].x,kq[i].y,kq[i].z,kq[i].w);
        sts128(ta+i*TBL+16, __byte_perm(kq[i].x,kq[i].y,0x5432), __byte_perm(kq[i].y,kq[i].z,0x5432), __byte_perm(kq[i].z,kq[i].w,0x5432), __byte_perm(kq[i].w,kn[i],0x5432));
        if(tid==0) sts128(sb+OFF_TBL+i*TBL+48, 0,0,0, kq[i].x<<16);
      }
    }
    STAMP(80+wg);
    {
      #pragma unroll
      for(int r=0;r<2;r++){
        const uint32_t w[8]={xq[2*r].x,xq[2*r].y,xq[2*r].z,xq[2*r].w,xq[2*r+1].x,xq[2*r+1].y,xq[2*r+1].z,xq[2*r+1].w};
        float s=0.f;
        #pragma unroll
        for(int i=0;i<8;i++) s+=bf_lo(w[i])+bf_hi(w[i]);
        #pragma unroll
        for(int o=16;o;o>>=1) s+=__shfl_xor_sync(~0u,s,o);
        const float m=s*(1.f/512); float d=0.f;
        #pragma unroll
        for(int i=0;i<8;i++){ const float a=bf_lo(w[i])-m, c2=bf_hi(w[i])-m; d=fmaf(a,a,d); d=fmaf(c2,c2,d); }
        #pragma unroll
        for(int o=16;o;o>>=1) d+=__shfl_xor_sync(~0u,d,o);
        const float rs=1.f/rbf(sqrtf(rbf(rbf(d*(1.f/512))+1e-5f)));
        const uint32_t mm=pack_bf16(m,m);
        uint32_t a[8];
        #pragma unroll
        for(int i=0;i<8;i++){ const uint32_t dd=hsub2_bf16(w[i],mm); a[i]=pack_bf16(bf_lo(dd)*rs,bf_hi(dd)*rs); }
        const uint32_t qa = sb+OFF_Q+(2*warp+r)*QP+lane*16;
        sts128(qa, w[0],w[1],w[2],w[3]); sts128(qa+512, w[4],w[5],w[6],w[7]);
        sts128(qa+16*QP, a[0],a[1],a[2],a[3]); sts128(qa+16*QP+512, a[4],a[5],a[6],a[7]);
      }
      asm volatile("bar.sync 1, 256;":::"memory");
      const int arr = warp>>2, part = (warp>>1)&1;
      const uint32_t la = sb+OFF_Q+(arr*16+part*8+2*(lane>>3)+(lane&1))*QP + ((lane&7)>>1)*16 + (warp&1)*512;
      const int chg = 8*t+g;
      uint4* dst = &g_xa[((((warp&1)*64+(chg>>2))*2+part)*128+b)*8 + ((arr*4+(chg&3))^(b&7))];
      #pragma unroll
      for(int i=0;i<8;i++){ uint4 v; ldsm4t(la+i*64, v.x,v.y,v.z,v.w); dst[i*8*2048]=v; }
      asm volatile("bar.sync 1, 256;":::"memory");
      if(tid==0){ asm volatile("fence.proxy.async.global;":::"memory"); signal_add(&g_cnt[0]); }
      __syncwarp();
    }
    STAMP(82+wg);
    asm volatile("barrier.cluster.wait.aligned;":::"memory");
    {
      const int c=lane>>3, p=g&1;
      uint32_t tb[5];
      #pragma unroll
      for(int s=0;s<5;s++){ const int y=16*c+wq+t+p+4*s; const int id=8*(y>>2)+4*(1-p)+(y&3); tb[s]=sb+OFF_TBL+wg*2*TBL+((id^(((id>>5)&3)<<3))<<2); }
      const uint64_t du = make_desc(sb+OFF_U+wg*2*UCH, UPL, 128, 0);
      const bool dsel = (c==0 && t==3-wq);
      const uint32_t dv0 = dsel ? (p? (dbits&0xffffu) : (dbits<<16)) : 0u, dv1 = dsel ? (p? (dbits>>16) : (dbits&0xffff0000u)) : 0u;
      float aE[2][32], aL[2][32];
      #pragma unroll
      for(int i=0;i<32;i++){ aE[0][i]=0.f; aE[1][i]=0.f; aL[0][i]=0.f; aL[1][i]=0.f; }
      uint32_t R[2][2][5];
      bf16* hdst = g_hT + (b*4+wg*2)*2048 + (tid&127)*8;
      const uint32_t xoff = (tid&127)*128;
#define U_MA(U) ((U)<16 ? 15-2*((U)>>2)-(((U)>>1)&1) : 15-2*(4+(((U)-16)>>1)))
#define U_MB(U) ((U)<16 ? U_MA(U)-8 : U_MA(U)-1)
#define CONV_LOAD(U) { conv_lda(R[(U)&1][0],tb,((U)&1)*TBL+U_MA(U)*512); conv_lda(R[(U)&1][1],tb,((U)&1)*TBL+U_MB(U)*512); }
#define CONV_GATE(T) { mbar_wait_cl(bar+8*(B_U+T),0); asm volatile("fence.proxy.async.shared::cta;":::"memory"); STAMP(8+wg*16+T); }
#define CONV_UNIT(U) { \
        wg_fence(); \
        if constexpr((U)<16){ conv_mma<128-8*U_MA(U)>(aL[(U)&1],R[(U)&1][0],du+((U)&1)*(UCH/16)+8*U_MA(U)); conv_mma<128-8*U_MA(U)>(aE[(U)&1],R[(U)&1][1],du+((U)&1)*(UCH/16)+8*U_MA(U)); \
          if constexpr((U)>=14) wgmma_rs<64,0>(aE[(U)&1],0u,((U)&1)?dv1:dv0,((U)&1)?dv1:dv0,0u,du+((U)&1)*(UCH/16)+64,1); } \
        else { conv_mma<64>(aL[(U)&1],R[(U)&1][0],du+((U)&1)*(UCH/16)+8*U_MA(U)); conv_mma<64>(aL[(U)&1],R[(U)&1][1],du+((U)&1)*(UCH/16)+8*U_MB(U)); \
          if constexpr((U)>=22) wgmma_rs<64,0>(aL[(U)&1],0u,((U)&1)?dv1:dv0,((U)&1)?dv1:dv0,0u,du+((U)&1)*(UCH/16),1); } \
        wg_commit(); wg_wait<1>(); \
        if constexpr((U)>0 && (U)<23) CONV_LOAD((U)+1) }
      CONV_LOAD(0) CONV_LOAD(1)
      CONV_GATE(0) CONV_UNIT(0)  CONV_UNIT(1)  CONV_UNIT(2)  CONV_UNIT(3)
      CONV_GATE(1) CONV_UNIT(4)  CONV_UNIT(5)  CONV_UNIT(6)  CONV_UNIT(7)
      CONV_GATE(2) CONV_UNIT(8)  CONV_UNIT(9)  CONV_UNIT(10) CONV_UNIT(11)
      CONV_GATE(3) CONV_UNIT(12) CONV_UNIT(13) CONV_UNIT(14) CONV_UNIT(15)
      CONV_GATE(4) CONV_UNIT(16) CONV_UNIT(17)
      mbar_wait(bar+8*(B_XA+1),0);
      conv_epi(aE[0],0.f,0.f,0.f,0.f,lane,sb+OFF_XAE+xoff,wg*2,hdst);
      CONV_GATE(5) CONV_UNIT(18) CONV_UNIT(19)
      conv_epi(aE[1],0.f,0.f,0.f,0.f,lane,sb+OFF_XAE+xoff,wg*2+1,hdst+2048);
      __syncwarp();
      if(lane==0){ mbar_arrive(bar+8*B_HD); mbar_arrive(bar+8*(B_WEMPTY+4)); mbar_arrive(bar+8*(B_WEMPTY+0)); mbar_arrive(bar+8*(B_WEMPTY+1)); }
      STAMP(84+wg);
      CONV_GATE(6) CONV_UNIT(20) CONV_UNIT(21)
      CONV_GATE(7)
      if(lane==0){ mbar_arrive(bar+8*(B_WEMPTY+2)); mbar_arrive(bar+8*(B_WEMPTY+3)); }
      CONV_UNIT(22) CONV_UNIT(23)
      mbar_wait(bar+8*B_XA,0);
      conv_epi(aL[0],aE[0][0],aE[0][1],aE[0][2],aE[0][3],lane,sb+OFF_XAL+xoff,wg*2,hdst+1024);
      wg_wait<0>();
      STAMP(86+wg);
      conv_epi(aL[1],aE[1][0],aE[1][1],aE[1][2],aE[1][3],lane,sb+OFF_XAL+xoff,wg*2+1,hdst+2048+1024);
      __syncwarp();
      if(lane==0){ mbar_arrive(bar+8*(B_HD+1)); mbar_arrive(bar+8*(B_WEMPTY+5)); }
      STAMP(88+wg);
    }
    const uint32_t xempty_cl = mapa(bar+8*(B_XEMPTY+wg*NX), lane&1);
    float ag[88], au[88];
    const uint32_t xbase = sb+OFF_X+wg*NX*XSLOT;
    int slot=0, ph=0, pslot=0;
    #pragma unroll 1
    for(int xi=0; xi<8; xi++){
      mbar_wait(bar+8*(B_XFULL+wg*NX+(xi&3)), xi>>2);
      const uint32_t xa = xbase+(xi&3)*XSLOT;
      #pragma unroll
      for(int hf=0; hf<2; hf++){
        mbar_wait(bar+8*(B_WFULL+slot), ph);
        if(xi==0 && hf==0) STAMP(1+wg*16);
        if(LEAD>0 && wg==1 && xi*2+hf==16-LEAD) asm volatile("bar.sync 1, 256;":::"memory");
        const uint64_t da = make_desc(xa+hf*4096, 0, 1024, 1);
        const uint64_t db = make_desc(sb+OFF_W+(5-slot)*WSLOT, 4096, 1024, 1);
        wg_fence();
        const int acc = (xi|hf);
        wgmma_ss<176,1,1>(ag, da,     db,         acc);
        wgmma_ss<176,1,1>(au, da,     db+768,     acc);
        wgmma_ss<176,1,1>(ag, da+128, db+128,     1);
        wgmma_ss<176,1,1>(au, da+128, db+768+128, 1);
        wg_commit();
        if(LEAD>0 && wg==0 && xi*2+hf==15) asm volatile("bar.arrive 1, 256;":::"memory");
        wg_wait<1>();
        if(acc){
          if(lane==0) mbar_arrive(bar+8*(B_WEMPTY+pslot));
          if(hf==0 && (lane>>1)==1) mbar_arrive_cl(xempty_cl+8*((xi-1)&3));
        }
        pslot=slot;
        if(++slot==NS){ slot=0; ph^=1; }
      }
    }
    mbar_wait(bar+8*(B_PAR+wg), 0);
    const float2 p0=*(const float2*)(smem_raw+OFF_ROW+(wg*64+wq*16+g)*8), p1=*(const float2*)(smem_raw+OFF_ROW+(wg*64+wq*16+g+8)*8);
    const float nm0=p0.x, r0=p0.y, nm1=p1.x, r1=p1.y;
    wg_wait<0>();
    STAMP(2+wg*16);
    if(lane==0){ mbar_arrive(bar+8*(B_WEMPTY+pslot)); mbar_arrive_cl(mapa(bar+8*(B_PRDY+wg), rank^1)); }
    uint32_t act[44], actp[44];
    const uint32_t adst = mapa(xbase+wq*8192+lane*16, rank^1), abar = mapa(bar+8*(B_AFULL+wg), rank^1);
    {
      const float4* cs = (const float4*)(smem_raw+OFF_CS);
      const float h0=0.5f*r0, h1=0.5f*r1, sc0=h0*r0, sc1=h1*r1;
      mbar_wait(bar+8*(B_PRDY+wg), 0);
      #pragma unroll
      for(int j=0;j<22;j++){
        const float4 c4=cs[4*j+t];
        const float g0=fmaf(nm0,c4.x,ag[4*j+0]), g1=fmaf(nm0,c4.y,ag[4*j+1]), g2=fmaf(nm1,c4.x,ag[4*j+2]), g3=fmaf(nm1,c4.y,ag[4*j+3]);
        const float y0=g0*fmaf(nm0,c4.z,au[4*j+0]), y1=g1*fmaf(nm0,c4.w,au[4*j+1]), y2=g2*fmaf(nm1,c4.z,au[4*j+2]), y3=g3*fmaf(nm1,c4.w,au[4*j+3]);
        act[2*j]  =pack_bf16(y0*fmaf(sc0,tanh_fast(g0*h0),sc0), y1*fmaf(sc0,tanh_fast(g1*h0),sc0));
        act[2*j+1]=pack_bf16(y2*fmaf(sc1,tanh_fast(g2*h1),sc1), y3*fmaf(sc1,tanh_fast(g3*h1),sc1));
        if((j&3)==3 && (j>>2)<NIN){ const int kk=j>>2; st_async128(adst+kk*512, act[4*kk],act[4*kk+1],act[4*kk+2],act[4*kk+3], abar); }
      }
    }
    STAMP(3+wg*16);
    float acc2[2][32];
    const uint32_t wbase = xbase+wq*8192;
    const uint32_t st_off = ((lane>>3)&1)*1024 + (7-(lane&7))*128;
    const int orow0 = pos2row(wg*1024+rt*64+wq*16+7), orow1 = pos2row(wg*1024+rt*64+wq*16+15);
    auto flush=[&](const float* a, int c){
      #pragma unroll
      for(int kk=0;kk<4;kk++)
        stsm4_nm(wbase+c*2048+st_off+(((2*kk+(lane>>4))^(7-(lane&7)))<<4), pack_bf16(a[8*kk],a[8*kk+1]), pack_bf16(a[8*kk+2],a[8*kk+3]), pack_bf16(a[8*kk+4],a[8*kk+5]), pack_bf16(a[8*kk+6],a[8*kk+7]));
      asm volatile("fence.proxy.async.shared::cta;":::"memory");
      __syncwarp();
      if(elect_one()){
        const int col = rank*256+((fp+c)&3)*64;
        tma3d_red_add(&maps.out, col, orow0&127, orow0>>7, wbase+c*2048);
        tma3d_red_add(&maps.out, col, orow1&127, orow1>>7, wbase+c*2048+1024);
        asm volatile("cp.async.bulk.commit_group;":::"memory");
      }
    };
    #pragma unroll
    for(int i=0;i<8;i++){
      const int ch = (G2_CH>>(4*i))&3, peer = (G2_PEER>>i)&1;
      const bool firstpeer = peer && ((G2_PEER & ((1u<<i)-1))==0);
      const int pch = i>0 ? (G2_CH>>(4*(i-1)))&3 : 0; const bool pdone = i>0 && ((G2_PEER>>(i-1))&1);
      if(firstpeer){
        mbar_wait(bar+8*(B_INIT+wg), 0);
        mbar_wait_cl(bar+8*(B_AFULL+wg), 0);
        #pragma unroll
        for(int kk=0;kk<11;kk++) lds128(wbase+lane*16+kk*512, actp[4*kk],actp[4*kk+1],actp[4*kk+2],actp[4*kk+3]);
      }
      mbar_wait(bar+8*(B_WFULL+slot), ph);
      const uint64_t db = make_desc(sb+OFF_W+(5-slot)*WSLOT, 0, 1024, 1);
      wg_fence();
      #pragma unroll
      for(int kk=0;kk<11;kk++){
        if(peer) wgmma_rs<64,1>(acc2[ch&1], actp[4*kk],actp[4*kk+1],actp[4*kk+2],actp[4*kk+3], db+kk*128, 1);
        else     wgmma_rs<64,1>(acc2[ch&1], act[4*kk],act[4*kk+1],act[4*kk+2],act[4*kk+3], db+kk*128, kk>0);
        if(i==0 && kk>=NIN) st_async128(adst+kk*512, act[4*kk],act[4*kk+1],act[4*kk+2],act[4*kk+3], abar);
      }
      wg_commit();
      if(i>0){
        wg_wait<1>();
        if(lane==0) mbar_arrive(bar+8*(B_WEMPTY+pslot));
        if(pdone) flush(acc2[pch&1], pch);
      }
      pslot=slot;
      if(++slot==NS){ slot=0; ph^=1; }
      STAMP(32+wg*16+i);
    }
    wg_wait<0>();
    STAMP(4+wg*16);
    flush(acc2[1], 3);
    STAMP(5+wg*16);
    asm volatile("cp.async.bulk.wait_group.read 0;":::"memory");
    STAMP(6+wg*16);
  }
  __syncwarp();
  asm volatile("barrier.cluster.arrive.relaxed.aligned;":::"memory");
  asm volatile("barrier.cluster.wait.aligned;":::"memory");
}

typedef CUresult (*PFN_encodeTiled)(CUtensorMap*, CUtensorMapDataType, cuuint32_t, void*, const cuuint64_t*, const cuuint64_t*, const cuuint32_t*, const cuuint32_t*, CUtensorMapInterleave, CUtensorMapSwizzle, CUtensorMapL2promotion, CUtensorMapFloatOOBfill);
static void make2d(PFN_encodeTiled enc, CUtensorMap* m, const void* p, uint64_t d0, uint64_t d1, uint32_t b0, uint32_t b1){
  cuuint64_t gd[2]={d0,d1}; cuuint64_t gs[1]={d0*2}; cuuint32_t bx[2]={b0,b1}; cuuint32_t es[2]={1,1};
  enc(m,CU_TENSOR_MAP_DATA_TYPE_BFLOAT16,2,(void*)p,gd,gs,bx,es,CU_TENSOR_MAP_INTERLEAVE_NONE,CU_TENSOR_MAP_SWIZZLE_128B,CU_TENSOR_MAP_L2_PROMOTION_L2_128B,CU_TENSOR_MAP_FLOAT_OOB_FILL_NONE);
}
static void make3d(PFN_encodeTiled enc, CUtensorMap* m, const void* p, uint64_t d0, uint64_t d1, uint64_t d2, uint64_t s1, uint64_t s2, uint32_t b0, uint32_t b1, uint32_t b2, CUtensorMapSwizzle sw, CUtensorMapL2promotion pr){
  cuuint64_t gd[3]={d0,d1,d2}; cuuint64_t gs[2]={s1,s2}; cuuint32_t bx[3]={b0,b1,b2}; cuuint32_t es[3]={1,1,1};
  enc(m,CU_TENSOR_MAP_DATA_TYPE_BFLOAT16,3,(void*)p,gd,gs,bx,es,CU_TENSOR_MAP_INTERLEAVE_NONE,sw,pr,CU_TENSOR_MAP_FLOAT_OOB_FILL_NONE);
}

extern "C" void kernel_launch(void* const* d_in, const int* in_sizes, int n_in, void* d_out, int out_size){
  const bf16* q=(const bf16*)d_in[0]; const bf16* k=(const bf16*)d_in[1]; const bf16* v=(const bf16*)d_in[2];
  const bf16* sh=(const bf16*)d_in[3]; const bf16* K=(const bf16*)d_in[4]; const bf16* Dv=(const bf16*)d_in[5];
  const bf16* wgt=(const bf16*)d_in[7]; const bf16* wup=(const bf16*)d_in[8]; const bf16* wdn=(const bf16*)d_in[9];
  void* fn=nullptr; cudaDriverEntryPointQueryResult qr; cudaGetDriverEntryPoint("cuTensorMapEncodeTiled",&fn,cudaEnableDefault,&qr);
  PFN_encodeTiled enc=(PFN_encodeTiled)fn;
  void* hT; cudaGetSymbolAddress(&hT,g_hT);
  Maps maps;
  make3d(enc,&maps.k,k,512,256,8,8192,1024,8,17,8,CU_TENSOR_MAP_SWIZZLE_NONE,CU_TENSOR_MAP_L2_PROMOTION_L2_128B);
  make3d(enc,&maps.v,v,512,256,8,8192,1024,8,16,8,CU_TENSOR_MAP_SWIZZLE_NONE,CU_TENSOR_MAP_L2_PROMOTION_L2_128B);
  make2d(enc,&maps.wg64,wgt,F_,D_,64,32); make2d(enc,&maps.wg48,wgt,F_,D_,48,32);
  make2d(enc,&maps.wu64,wup,F_,D_,64,32); make2d(enc,&maps.wu48,wup,F_,D_,48,32);
  make2d(enc,&maps.wd,wdn,D_,F_,64,176);
  make2d(enc,&maps.ht,hT,S_,D_,64,32);
  make3d(enc,&maps.out,d_out,512,128,16,1024,131072,64,1,8,CU_TENSOR_MAP_SWIZZLE_128B,CU_TENSOR_MAP_L2_PROMOTION_NONE);
  cudaFuncSetAttribute(fused_kernel,cudaFuncAttributeMaxDynamicSharedMemorySize,SMEM_BYTES);
  fused_kernel<<<128,384,SMEM_BYTES>>>(maps,q,sh,K,Dv,(bf16*)d_out);
}
```

```cpp
#include <cuda_runtime.h>
#include <cuda_bf16.h>
#include <cuda.h>
#include <stdint.h>

template<int TA,int TB> __device__ __forceinline__ void wgmma_ss_n176(float* d, uint64_t da, uint64_t db, int sd){
  asm volatile("{ .reg .pred p; setp.ne.b32 p, %90, 0; wgmma.mma_async.sync.aligned.m64n176k16.f32.bf16.bf16 {%0,%1,%2,%3,%4,%5,%6,%7,%8,%9,%10,%11,%12,%13,%14,%15,%16,%17,%18,%19,%20,%21,%22,%23,%24,%25,%26,%27,%28,%29,%30,%31,%32,%33,%34,%35,%36,%37,%38,%39,%40,%41,%42,%43,%44,%45,%46,%47,%48,%49,%50,%51,%52,%53,%54,%55,%56,%57,%58,%59,%60,%61,%62,%63,%64,%65,%66,%67,%68,%69,%70,%71,%72,%73,%74,%75,%76,%77,%78,%79,%80,%81,%82,%83,%84,%85,%86,%87}, %88, %89, p, 1, 1, %91, %92; }"
   : "+f"(d[0]),"+f"(d[1]),"+f"(d[2]),"+f"(d[3]),"+f"(d[4]),"+f"(d[5]),"+f"(d[6]),"+f"(d[7]),"+f"(d[8]),"+f"(d[9]),"+f"(d[10]),"+f"(d[11]),"+f"(d[12]),"+f"(d[13]),"+f"(d[14]),"+f"(d[15]),"+f"(d[16]),"+f"(d[17]),"+f"(d[18]),"+f"(d[19]),"+f"(d[20]),"+f"(d[21]),"+f"(d[22]),"+f"(d[23]),"+f"(d[24]),"+f"(d[25]),"+f"(d[26]),"+f"(d[27]),"+f"(d[28]),"+f"(d[29]),"+f"(d[30]),"+f"(d[31]),"+f"(d[32]),"+f"(d[33]),"+f"(d[34]),"+f"(d[35]),"+f"(d[36]),"+f"(d[37]),"+f"(d[38]),"+f"(d[39]),"+f"(d[40]),"+f"(d[41]),"+f"(d[42]),"+f"(d[43]),"+f"(d[44]),"+f"(d[45]),"+f"(d[46]),"+f"(d[47]),"+f"(d[48]),"+f"(d[49]),"+f"(d[50]),"+f"(d[51]),"+f"(d[52]),"+f"(d[53]),"+f"(d[54]),"+f"(d[55]),"+f"(d[56]),"+f"(d[57]),"+f"(d[58]),"+f"(d[59]),"+f"(d[60]),"+f"(d[61]),"+f"(d[62]),"+f"(d[63]),"+f"(d[64]),"+f"(d[65]),"+f"(d[66]),"+f"(d[67]),"+f"(d[68]),"+f"(d[69]),"+f"(d[70]),"+f"(d[71]),"+f"(d[72]),"+f"(d[73]),"+f"(d[74]),"+f"(d[75]),"+f"(d[76]),"+f"(d[77]),"+f"(d[78]),"+f"(d[79]),"+f"(d[80]),"+f"(d[81]),"+f"(d[82]),"+f"(d[83]),"+f"(d[84]),"+f"(d[85]),"+f"(d[86]),"+f"(d[87]) : "l"(da), "l"(db), "r"(sd), "n"(TA), "n"(TB));
}
template<int TB> __device__ __forceinline__ void wgmma_rs_n8(float* d, uint32_t a0, uint32_t a1, uint32_t a2, uint32_t a3, uint64_t db, int sd){
  asm volatile("{ .reg .pred p; setp.ne.b32 p, %9, 0; wgmma.mma_async.sync.aligned.m64n8k16.f32.bf16.bf16 {%0,%1,%2,%3}, {%4,%5,%6,%7}, %8, p, 1, 1, %10; }"
   : "+f"(d[0]),"+f"(d[1]),"+f"(d[2]),"+f"(d[3]) : "r"(a0),"r"(a1),"r"(a2),"r"(a3), "l"(db), "r"(sd), "n"(TB));
}
template<int TB> __device__ __forceinline__ void wgmma_rs_n16(float* d, uint32_t a0, uint32_t a1, uint32_t a2, uint32_t a3, uint64_t db, int sd){
  asm volatile("{ .reg .pred p; setp.ne.b32 p, %13, 0; wgmma.mma_async.sync.aligned.m64n16k16.f32.bf16.bf16 {%0,%1,%2,%3,%4,%5,%6,%7}, {%8,%9,%10,%11}, %12, p, 1, 1, %14; }"
   : "+f"(d[0]),"+f"(d[1]),"+f"(d[2]),"+f"(d[3]),"+f"(d[4]),"+f"(d[5]),"+f"(d[6]),"+f"(d[7]) : "r"(a0),"r"(a1),"r"(a2),"r"(a3), "l"(db), "r"(sd), "n"(TB));
}
template<int TB> __device__ __forceinline__ void wgmma_rs_n24(float* d, uint32_t a0, uint32_t a1, uint32_t a2, uint32_t a3, uint64_t db, int sd){
  asm volatile("{ .reg .pred p; setp.ne.b32 p, %17, 0; wgmma.mma_async.sync.aligned.m64n24k16.f32.bf16.bf16 {%0,%1,%2,%3,%4,%5,%6,%7,%8,%9,%10,%11}, {%12,%13,%14,%15}, %16, p, 1, 1, %18; }"
   : "+f"(d[0]),"+f"(d[1]),"+f"(d[2]),"+f"(d[3]),"+f"(d[4]),"+f"(d[5]),"+f"(d[6]),"+f"(d[7]),"+f"(d[8]),"+f"(d[9]),"+f"(d[10]),"+f"(d[11]) : "r"(a0),"r"(a1),"r"(a2),"r"(a3), "l"(db), "r"(sd), "n"(TB));
}
template<int TB> __device__ __forceinline__ void wgmma_rs_n32(float* d, uint32_t a0, uint32_t a1, uint32_t a2, uint32_t a3, uint64_t db, int sd){
  asm volatile("{ .reg .pred p; setp.ne.b32 p, %21, 0; wgmma.mma_async.sync.aligned.m64n32k16.f32.bf16.bf16 {%0,%1,%2,%3,%4,%5,%6,%7,%8,%9,%10,%11,%12,%13,%14,%15}, {%16,%17,%18,%19}, %20, p, 1, 1, %22; }"
   : "+f"(d[0]),"+f"(d[1]),"+f"(d[2]),"+f"(d[3]),"+f"(d[4]),"+f"(d[5]),"+f"(d[6]),"+f"(d[7]),"+f"(d[8]),"+f"(d[9]),"+f"(d[10]),"+f"(d[11]),"+f"(d[12]),"+f"(d[13]),"+f"(d[14]),"+f"(d[15]) : "r"(a0),"r"(a1),"r"(a2),"r"(a3), "l"(db), "r"(sd), "n"(TB));
}
template<int TB> __device__ __forceinline__ void wgmma_rs_n40(float* d, uint32_t a0, uint32_t a1, uint32_t a2, uint32_t a3, uint64_t db, int sd){
  asm volatile("{ .reg .pred p; setp.ne.b32 p, %25, 0; wgmma.mma_async.sync.aligned.m64n40k16.f32.bf16.bf16 {%0,%1,%2,%3,%4,%5,%6,%7,%8,%9,%10,%11,%12,%13,%14,%15,%16,%17,%18,%19}, {%20,%21,%22,%23}, %24, p, 1, 1, %26; }"
   : "+f"(d[0]),"+f"(d[1]),"+f"(d[2]),"+f"(d[3]),"+f"(d[4]),"+f"(d[5]),"+f"(d[6]),"+f"(d[7]),"+f"(d[8]),"+f"(d[9]),"+f"(d[10]),"+f"(d[11]),"+f"(d[12]),"+f"(d[13]),"+f"(d[14]),"+f"(d[15]),"+f"(d[16]),"+f"(d[17]),"+f"(d[18]),"+f"(d[19]) : "r"(a0),"r"(a1),"r"(a2),"r"(a3), "l"(db), "r"(sd), "n"(TB));
}
template<int TB> __device__ __forceinline__ void wgmma_rs_n48(float* d, uint32_t a0, uint32_t a1, uint32_t a2, uint32_t a3, uint64_t db, int sd){
  asm volatile("{ .reg .pred p; setp.ne.b32 p, %29, 0; wgmma.mma_async.sync.aligned.m64n48k16.f32.bf16.bf16 {%0,%1,%2,%3,%4,%5,%6,%7,%8,%9,%10,%11,%12,%13,%14,%15,%16,%17,%18,%19,%20,%21,%22,%23}, {%24,%25,%26,%27}, %28, p, 1, 1, %30; }"
   : "+f"(d[0]),"+f"(d[1]),"+f"(d[2]),"+f"(d[3]),"+f"(d[4]),"+f"(d[5]),"+f"(d[6]),"+f"(d[7]),"+f"(d[8]),"+f"(d[9]),"+f"(d[10]),"+f"(d[11]),"+f"(d[12]),"+f"(d[13]),"+f"(d[14]),"+f"(d[15]),"+f"(d[16]),"+f"(d[17]),"+f"(d[18]),"+f"(d[19]),"+f"(d[20]),"+f"(d[21]),"+f"(d[22]),"+f"(d[23]) : "r"(a0),"r"(a1),"r"(a2),"r"(a3), "l"(db), "r"(sd), "n"(TB));
}
template<int TB> __device__ __forceinline__ void wgmma_rs_n56(float* d, uint32_t a0, uint32_t a1, uint32_t a2, uint32_t a3, uint64_t db, int sd){
  asm volatile("{ .reg .pred p; setp.ne.b32 p, %33, 0; wgmma.mma_async.sync.aligned.m64n56k16.f32.bf16.bf16 {%0,%1,%2,%3,%4,%5,%6,%7,%8,%9,%10,%11,%12,%13,%14,%15,%16,%17,%18,%19,%20,%21,%22,%23,%24,%25,%26,%27}, {%28,%29,%30,%31}, %32, p, 1, 1, %34; }"
   : "+f"(d[0]),"+f"(d[1]),"+f"(d[2]),"+f"(d[3]),"+f"(d[4]),"+f"(d[5]),"+f"(d[6]),"+f"(d[7]),"+f"(d[8]),"+f"(d[9]),"+f"(d[10]),"+f"(d[11]),"+f"(d[12]),"+f"(d[13]),"+f"(d[14]),"+f"(d[15]),"+f"(d[16]),"+f"(d[17]),"+f"(d[18]),"+f"(d[19]),"+f"(d[20]),"+f"(d[21]),"+f"(d[22]),"+f"(d[23]),"+f"(d[24]),"+f"(d[25]),"+f"(d[26]),"+f"(d[27]) : "r"(a0),"r"(a1),"r"(a2),"r"(a3), "l"(db), "r"(sd), "n"(TB));
}
template<int TB> __device__ __forceinline__ void wgmma_rs_n64(float* d, uint32_t a0, uint32_t a1, uint32_t a2, uint32_t a3, uint64_t db, int sd){
  asm volatile("{ .reg .pred p; setp.ne.b32 p, %37, 0; wgmma.mma_async.sync.aligned.m64n64k16.f32.bf16.bf16 {%0,%1,%2,%3,%4,%5,%6,%7,%8,%9,%10,%11,%12,%13,%14,%15,%16,%17,%18,%19,%20,%21,%22,%23,%24,%25,%26,%27,%28,%29,%30,%31}, {%32,%33,%34,%35}, %36, p, 1, 1, %38; }"
   : "+f"(d[0]),"+f"(d[1]),"+f"(d[2]),"+f"(d[3]),"+f"(d[4]),"+f"(d[5]),"+f"(d[6]),"+f"(d[7]),"+f"(d[8]),"+f"(d[9]),"+f"(d[10]),"+f"(d[11]),"+f"(d[12]),"+f"(d[13]),"+f"(d[14]),"+f"(d[15]),"+f"(d[16]),"+f"(d[17]),"+f"(d[18]),"+f"(d[19]),"+f"(d[20]),"+f"(d[21]),"+f"(d[22]),"+f"(d[23]),"+f"(d[24]),"+f"(d[25]),"+f"(d[26]),"+f"(d[27]),"+f"(d[28]),"+f"(d[29]),"+f"(d[30]),"+f"(d[31]) : "r"(a0),"r"(a1),"r"(a2),"r"(a3), "l"(db), "r"(sd), "n"(TB));
}
template<int N,int TA,int TB> __device__ __forceinline__ void wgmma_ss(float* d, uint64_t da, uint64_t db, int sd){
  if constexpr(N==176) wgmma_ss_n176<TA,TB>(d,da,db,sd);
}
template<int N,int TB> __device__ __forceinline__ void wgmma_rs(float* d, uint32_t a0,uint32_t a1,uint32_t a2,uint32_t a3, uint64_t db, int sd){
  if constexpr(N==8) wgmma_rs_n8<TB>(d,a0,a1,a2,a3,db,sd);
  if constexpr(N==16) wgmma_rs_n16<TB>(d,a0,a1,a2,a3,db,sd);
  if constexpr(N==24) wgmma_rs_n24<TB>(d,a0,a1,a2,a3,db,sd);
  if constexpr(N==32) wgmma_rs_n32<TB>(d,a0,a1,a2,a3,db,sd);
  if constexpr(N==40) wgmma_rs_n40<TB>(d,a0,a1,a2,a3,db,sd);
  if constexpr(N==48) wgmma_rs_n48<TB>(d,a0,a1,a2,a3,db,sd);
  if constexpr(N==56) wgmma_rs_n56<TB>(d,a0,a1,a2,a3,db,sd);
  if constexpr(N==64) wgmma_rs_n64<TB>(d,a0,a1,a2,a3,db,sd);
}

typedef __nv_bfloat16 bf16;
constexpr int S_ = 2048, D_ = 512, F_ = 1376, FS = 176;

__device__ __forceinline__ uint32_t smem_u32(const void* p){ return (uint32_t)__cvta_generic_to_shared(p); }
__device__ __forceinline__ void mbar_init(uint32_t bar, uint32_t cnt){ asm volatile("mbarrier.init.shared::cta.b64 [%0], %1;"::"r"(bar),"r"(cnt):"memory"); }
__device__ __forceinline__ void mbar_expect_tx(uint32_t bar, uint32_t bytes){ asm volatile("mbarrier.arrive.expect_tx.shared::cta.b64 _, [%0], %1;"::"r"(bar),"r"(bytes):"memory"); }
__device__ __forceinline__ void mbar_arrive(uint32_t bar){ asm volatile("mbarrier.arrive.shared::cta.b64 _, [%0];"::"r"(bar):"memory"); }
__device__ __forceinline__ void mbar_arrive_n(uint32_t bar, uint32_t n){ asm volatile("mbarrier.arrive.shared::cta.b64 _, [%0], %1;"::"r"(bar),"r"(n):"memory"); }
__device__ __forceinline__ void mbar_arrive_cl(uint32_t cbar){ asm volatile("mbarrier.arrive.shared::cluster.b64 _, [%0];"::"r"(cbar):"memory"); }
__device__ __forceinline__ uint32_t mapa(uint32_t a, uint32_t cta){ uint32_t r; asm volatile("mapa.shared::cluster.u32 %0, %1, %2;":"=r"(r):"r"(a),"r"(cta)); return r; }
__device__ __forceinline__ void mbar_wait(uint32_t bar, uint32_t ph){
  asm volatile("{ .reg .pred p; .reg .u32 c; mov.u32 c, 0;\n"
               "WL: mbarrier.try_wait.parity.shared::cta.b64 p, [%0], %1; @p bra WD; add.u32 c,c,1; setp.lt.u32 p, c, 2000000; @p bra WL; trap;\n"
               "WD: }"::"r"(bar),"r"(ph):"memory"); }
__device__ __forceinline__ void spin_guard(int n){ asm volatile("{ .reg .pred p; setp.gt.s32 p, %0, 2000000; @p trap; }"::"r"(n)); }
__device__ __forceinline__ bool elect_one(){ uint32_t p; asm volatile("{ .reg .pred P; elect.sync _|P, 0xffffffff; selp.u32 %0,1,0,P; }":"=r"(p)); return p; }
__device__ __forceinline__ void tma2d(uint32_t dst, const CUtensorMap* m, int c0, int c1, uint32_t bar){
  asm volatile("cp.async.bulk.tensor.2d.shared::cluster.global.mbarrier::complete_tx::bytes [%0], [%1, {%3, %4}], [%2];"::"r"(dst),"l"(m),"r"(bar),"r"(c0),"r"(c1):"memory"); }
__device__ __forceinline__ void tma2d_mc(uint32_t dst, const CUtensorMap* m, int c0, int c1, uint32_t bar){
  asm volatile("cp.async.bulk.tensor.2d.shared::cluster.global.mbarrier::complete_tx::bytes.multicast::cluster [%0], [%1, {%3, %4}], [%2], %5;"::"r"(dst),"l"(m),"r"(bar),"r"(c0),"r"(c1),"h"((uint16_t)3):"memory"); }
__device__ __forceinline__ void cluster_sync(){ asm volatile("barrier.cluster.arrive.release.aligned; barrier.cluster.wait.acquire.aligned;":::"memory"); }
__device__ __forceinline__ void wg_fence(){ asm volatile("wgmma.fence.sync.aligned;":::"memory"); }
__device__ __forceinline__ void wg_commit(){ asm volatile("wgmma.commit_group.sync.aligned;":::"memory"); }
template<int N> __device__ __forceinline__ void wg_wait(){ asm volatile("wgmma.wait_group.sync.aligned %0;"::"n"(N):"memory"); }
__device__ __forceinline__ uint64_t make_desc(uint32_t addr, uint32_t lbo, uint32_t sbo, uint32_t sw){ return (uint64_t)((addr&0x3FFFF)>>4) | ((uint64_t)((lbo&0x3FFFF)>>4)<<16) | ((uint64_t)((sbo&0x3FFFF)>>4)<<32) | ((uint64_t)sw<<62); }
__device__ __forceinline__ void ldsm4t(uint32_t a, uint32_t& r0, uint32_t& r1, uint32_t& r2, uint32_t& r3){ asm volatile("ldmatrix.sync.aligned.m8n8.x4.trans.shared.b16 {%0,%1,%2,%3}, [%4];":"=r"(r0),"=r"(r1),"=r"(r2),"=r"(r3):"r"(a):"memory"); }
__device__ __forceinline__ void stsm4(uint32_t a, uint32_t r0, uint32_t r1, uint32_t r2, uint32_t r3){ asm volatile("stmatrix.sync.aligned.m8n8.x4.shared.b16 [%0], {%1,%2,%3,%4};"::"r"(a),"r"(r0),"r"(r1),"r"(r2),"r"(r3):"memory"); }
__device__ __forceinline__ uint32_t pack_bf16(float lo, float hi){ uint32_t r; asm("cvt.rn.bf16x2.f32 %0, %1, %2;":"=r"(r):"f"(hi),"f"(lo)); return r; }
__device__ __forceinline__ float bf_lo(uint32_t v){ return __uint_as_float(v<<16); }
__device__ __forceinline__ float bf_hi(uint32_t v){ return __uint_as_float(v&0xffff0000u); }
__device__ __forceinline__ float rbf(float x){ return __bfloat162float(__float2bfloat16(x)); }
__device__ __forceinline__ uint32_t hadd2_bf16(uint32_t a, uint32_t b){ uint32_t r; asm("add.rn.bf16x2 %0, %1, %2;":"=r"(r):"r"(a),"r"(b)); return r; }
__device__ __forceinline__ float tanh_fast(float x){ float r; asm("tanh.approx.f32 %0, %1;":"=f"(r):"f"(x)); return r; }

__device__ __forceinline__ void st_rlx128(void* p, uint32_t a, uint32_t b, uint32_t c, uint32_t d){
  asm volatile("{ .reg .b64 l,h; .reg .b128 v; mov.b64 l,{%1,%2}; mov.b64 h,{%3,%4}; mov.b128 v,{l,h}; st.relaxed.gpu.global.b128 [%0], v; }"::"l"(p),"r"(a),"r"(b),"r"(c),"r"(d):"memory"); }
__device__ __forceinline__ void ld_rlx128(const void* p, uint4& v){
  asm volatile("{ .reg .b64 l,h; .reg .b128 v; ld.relaxed.gpu.global.b128 v, [%4]; mov.b128 {l,h}, v; mov.b64 {%0,%1}, l; mov.b64 {%2,%3}, h; }":"=r"(v.x),"=r"(v.y),"=r"(v.z),"=r"(v.w):"l"(p):"memory"); }
__device__ __forceinline__ void st_async128(uint32_t dst, uint32_t a, uint32_t b, uint32_t c, uint32_t d, uint32_t cbar){
  asm volatile("st.async.weak.shared::cluster.mbarrier::complete_tx::bytes.v4.b32 [%0], {%1,%2,%3,%4}, [%5];"::"r"(dst),"r"(a),"r"(b),"r"(c),"r"(d),"r"(cbar)); }
__device__ __forceinline__ void st_async32(uint32_t dst, uint32_t a, uint32_t cbar){
  asm volatile("st.async.weak.shared::cluster.mbarrier::complete_tx::bytes.b32 [%0], %1, [%2];"::"r"(dst),"r"(a),"r"(cbar)); }
__device__ __forceinline__ void mbar_wait_nomem(uint32_t bar, uint32_t ph){
  asm volatile("{ .reg .pred p; .reg .u32 c; mov.u32 c, 0;\n"
               "WL: mbarrier.try_wait.parity.shared::cta.b64 p, [%0], %1; @p bra WD; add.u32 c,c,1; setp.lt.u32 p, c, 2000000; @p bra WL; trap;\n"
               "WD: }"::"r"(bar),"r"(ph)); }
__device__ __forceinline__ void bulk_g2s(uint32_t dst, const void* src, uint32_t bytes, uint32_t bar){
  asm volatile("cp.async.bulk.shared::cluster.global.mbarrier::complete_tx::bytes [%0], [%1], %2, [%3];"::"r"(dst),"l"(src),"r"(bytes),"r"(bar):"memory"); }
__device__ __forceinline__ void mbar_wait_cl(uint32_t bar, uint32_t ph){
  asm volatile("{ .reg .pred p; .reg .u32 c; mov.u32 c, 0;\n"
               "WL: mbarrier.try_wait.parity.acquire.cluster.shared::cta.b64 p, [%0], %1; @p bra WD; add.u32 c,c,1; setp.lt.u32 p, c, 2000000; @p bra WL; trap;\n"
               "WD: }"::"r"(bar),"r"(ph):"memory"); }
__device__ __forceinline__ void lds128(uint32_t a, uint32_t& x, uint32_t& y, uint32_t& z, uint32_t& w){ asm volatile("ld.shared.v4.u32 {%0,%1,%2,%3}, [%4];":"=r"(x),"=r"(y),"=r"(z),"=r"(w):"r"(a):"memory"); }
__device__ __forceinline__ void tma4d_red_add(const CUtensorMap* m, int c0, int c1, int c2, int c3, uint32_t src){
  asm volatile("cp.reduce.async.bulk.tensor.4d.global.shared::cta.add.tile.bulk_group [%0, {%1, %2, %3, %4}], [%5];"::"l"(m),"r"(c0),"r"(c1),"r"(c2),"r"(c3),"r"(src):"memory"); }
__device__ __forceinline__ void stsm4_nm(uint32_t a, uint32_t r0, uint32_t r1, uint32_t r2, uint32_t r3){ asm volatile("stmatrix.sync.aligned.m8n8.x4.shared.b16 [%0], {%1,%2,%3,%4};"::"r"(a),"r"(r0),"r"(r1),"r"(r2),"r"(r3)); }
__device__ __forceinline__ void tma3d(uint32_t dst, const CUtensorMap* m, int c0, int c1, int c2, uint32_t bar){
  asm volatile("cp.async.bulk.tensor.3d.shared::cluster.global.mbarrier::complete_tx::bytes [%0], [%1, {%3, %4, %5}], [%2];"::"r"(dst),"l"(m),"r"(bar),"r"(c0),"r"(c1),"r"(c2):"memory"); }
__device__ __forceinline__ uint32_t lds32(uint32_t a){ uint32_t v; asm volatile("ld.shared.u32 %0, [%1];":"=r"(v):"r"(a)); return v; }
__device__ __forceinline__ void sts128(uint32_t a, uint32_t x, uint32_t y, uint32_t z, uint32_t w){ asm volatile("st.shared.v4.u32 [%0], {%1,%2,%3,%4};"::"r"(a),"r"(x),"r"(y),"r"(z),"r"(w):"memory"); }
__device__ __forceinline__ uint4 ldg_nc128(const void* p){ uint4 v; asm volatile("ld.global.nc.L1::no_allocate.v4.u32 {%0,%1,%2,%3}, [%4];":"=r"(v.x),"=r"(v.y),"=r"(v.z),"=r"(v.w):"l"(p)); return v; }
__device__ __forceinline__ uint32_t hmul2_bf16(uint32_t a, uint32_t b){ uint32_t r; asm("mul.rn.bf16x2 %0, %1, %2;":"=r"(r):"r"(a),"r"(b)); return r; }
__device__ __forceinline__ uint32_t hfma2_bf16(uint32_t a, uint32_t b, uint32_t c){ uint32_t r; asm("fma.rn.bf16x2 %0, %1, %2, %3;":"=r"(r):"r"(a),"r"(b),"r"(c)); return r; }
__device__ __forceinline__ uint32_t hsub2_bf16(uint32_t a, uint32_t b){ uint32_t r; asm("sub.rn.bf16x2 %0, %1, %2;":"=r"(r):"r"(a),"r"(b)); return r; }
__device__ __forceinline__ void poll_ge(const unsigned* p, unsigned target){
  unsigned v; int n=0;
  do{ asm volatile("ld.acquire.gpu.global.u32 %0, [%1];":"=r"(v):"l"(p):"memory"); spin_guard(++n); }while((int)(v-target)<0); }
__device__ __forceinline__ void signal_add(unsigned* p){ asm volatile("fence.acq_rel.gpu;":::"memory"); asm volatile("red.relaxed.gpu.global.add.u32 [%0], 1;"::"l"(p):"memory"); }
__device__ __forceinline__ void lds128_nm(uint32_t a, uint32_t& x, uint32_t& y, uint32_t& z, uint32_t& w){ asm volatile("ld.shared.v4.u32 {%0,%1,%2,%3}, [%4];":"=r"(x),"=r"(y),"=r"(z),"=r"(w):"r"(a)); }
__device__ __forceinline__ float ln_rstd(float var){
  float sq, r; asm("sqrt.approx.f32 %0, %1;":"=f"(sq):"f"(rbf(rbf(var)+1e-5f))); asm("rcp.approx.f32 %0, %1;":"=f"(r):"f"(rbf(sq))); return r; }
__device__ __forceinline__ float4 gather_sum(const uint4* src, int n, int stride, uint32_t par){
  float4 c=make_float4(0.f,0.f,0.f,0.f);
  #pragma unroll 1
  for(int kb=0;kb<n;kb+=4){
    uint4 v[4]; int it=0;
    do{
      #pragma unroll
      for(int u=0;u<4;u++) ld_rlx128(src+u*stride, v[u]);
      spin_guard(++it);
    }while(((v[0].x^par)|(v[1].x^par)|(v[2].x^par)|(v[3].x^par))&1);
    #pragma unroll
    for(int u=0;u<4;u++){ c.x+=__uint_as_float(v[u].x); c.y+=__uint_as_float(v[u].y); c.z+=__uint_as_float(v[u].z); c.w+=__uint_as_float(v[u].w); }
    src+=4*stride;
  }
  return c;
}
__host__ __device__ __forceinline__ int pos2row(int pos){
  const int P = 1 - (pos >> 10), thr = (pos & 1023) >> 3, k = (pos>>2)&1, h = (pos>>1)&1, e = pos&1;
  const int w = thr >> 5, tp = (thr >> 3)&3, j = (thr >> 1)&3, p = thr & 1;
  return 16*(127 - (64*P + 16*j + 8*k + 2*tp + e)) + 8*h + 2*w + p;
}

__device__ __align__(1024) bf16 g_hT[D_*S_];
__device__ __align__(1024) uint4 g_xa[128*128*8];
__device__ __align__(1024) uint4 g_qs[128*8];
__device__ uint4 g_stat[16*2*8*32];
__device__ uint4 g_csp[8*16*88];
__device__ uint4 g_cs2[8*96];
__device__ __align__(512) unsigned g_hflag[2*32*32];
__device__ unsigned g_cnt[4*32];
#define STAMP(i)

#define RC 224
#define RP 56
#define STR2(x) #x
#define STR(x) STR2(x)
#define KVAHEAD 4
#define PACE 6
#define CGMAP(c) (c)
#define QDELAY 1700
#define WSTART 5
#define CSLEEP 600
#define KEPI 6
#define KV0 3
#define XPOS 4
#define PFE 0
#define CP 2
#define BARV 0
#define BSLEEP 20
#define WDPF 6
#define SKW 4
#define APOS 2
#define SEND0 1
#define NIN 5
#define LEAD 0
constexpr uint32_t G2_CH = 0x33221010u, G2_PEER = 0xAC;
constexpr int NS = 6, WSLOT = 24576, NX = 4, XSLOT = 8192;
constexpr int OFF_RES0 = 0, OFF_X = 8192, OFF_RES1 = 73728, OFF_W = 81920;
constexpr int OFF_CS = OFF_W + NS*WSLOT, OFF_ROW = OFF_CS + 2*FS*4, OFF_BAR = OFF_ROW + 1024;
constexpr int TBL = 8320, UPL = 2112, UCH = 2*UPL, QP = 1088, KVCH = 4224;
constexpr int OFF_TBL = 32768, OFF_U = OFF_TBL + 4*TBL, OFF_XAL = 83968, OFF_XAE = OFF_W + 1*WSLOT;
constexpr int OFF_IMG = 0, OFF_X8 = OFF_XAL + 16384;
#define KVOFF(T) (OFF_W + 3*WSLOT + (T)*KVCH - ((T)>>2)*(WSLOT+4*KVCH))
constexpr int OFF_KV = OFF_W + 3*WSLOT, OFF_Q = OFF_W + 4*WSLOT, OFF_SK = OFF_Q + 16*QP;
static_assert(OFF_U + 4*UCH <= OFF_XAL && OFF_XAL + 16384 <= OFF_W + WSLOT, "overlay");
constexpr int B_WFULL = 0, B_WEMPTY = B_WFULL+NS, B_XFULL = B_WEMPTY+NS, B_XEMPTY = B_XFULL+2*NX, B_PRDY = B_XEMPTY+2*NX, B_AFULL = B_PRDY+2,
              B_ONE = B_AFULL+2, B_RES = B_ONE, B_INIT = B_RES+2, B_XA = B_INIT+2, B_PAR = B_XA+2, B_TD = B_PAR+2, B_KV = B_TD+1, B_U = B_KV+8, B_HD = B_U+8, B_SK = B_HD+2, B_Q = B_SK+1, B_QD = B_Q+8, B_SC = B_QD+1, B_X03 = B_SC+1, B_PK = B_X03+1, NBAR = B_PK+1;
constexpr int OFF_MISC = (OFF_BAR + NBAR*8 + 15)&~15;
constexpr int SMEM_BYTES = OFF_MISC + 16;
static_assert(SMEM_BYTES<=232448,"smem");

struct Maps { CUtensorMap k, v, xa, wg64, wg48, wu64, wu48, wd, ht, out; };

__device__ __forceinline__ void load_w_stage(const Maps& maps, uint32_t dst, int col, int k0, uint32_t fb){
  tma2d(dst,            &maps.wg64, col,     k0, fb);
  tma2d(dst+4096,       &maps.wg64, col+64,  k0, fb);
  tma2d(dst+8192,       &maps.wg48, col+128, k0, fb);
  tma2d(dst+12288,      &maps.wu64, col,     k0, fb);
  tma2d(dst+12288+4096, &maps.wu64, col+64,  k0, fb);
  tma2d(dst+12288+8192, &maps.wu48, col+128, k0, fb);
}

template<int N> __device__ __forceinline__ void conv_mma(float* acc, const uint32_t* R, uint64_t db){
  wgmma_rs<N,0>(acc, R[0],R[1],R[2],R[3], db,   1);
  wgmma_rs<N,0>(acc, R[4],R[5],R[6],R[7], db+1, 1);
}
__device__ __forceinline__ void conv_lda(uint32_t* R, const uint32_t* tb, int off){
  R[0]=lds32(tb[0]+off); R[1]=lds32(tb[1]+off); R[3]=lds32(tb[2]+off); R[5]=lds32(tb[3]+off); R[7]=lds32(tb[4]+off);
}
__device__ __forceinline__ void conv_dup(uint32_t* R){
  asm volatile("mov.b32 %0, %1;":"=r"(R[2]):"r"(R[1])); asm volatile("mov.b32 %0, %1;":"=r"(R[4]):"r"(R[3])); asm volatile("mov.b32 %0, %1;":"=r"(R[6]):"r"(R[5]));
}
__device__ __forceinline__ void zero4(float* a){
  #pragma unroll
  for(int i=0;i<4;i++) asm volatile("mov.b32 %0, 0;":"=f"(a[i]));
}
__device__ __forceinline__ uint32_t tid_now(){ uint32_t t; asm volatile("mov.u32 %0, %%tid.x;":"=r"(t)); return t; }
template<int PART> __device__ __forceinline__ void load_xa(uint4* x, uint4* a, uint32_t sb, int warp, int lane){
  const int cb = CGMAP(blockIdx.x>>1)*2+(blockIdx.x&1);
  const uint32_t tw = (warp&3)*32+lane, pq = (PART*4)^(tw&7), pc = ((warp>>2)*2)^pq;
  uint4 st[4];
  #pragma unroll
  for(int i=0;i<2;i++) lds128(sb+OFF_XAL+tw*128+((pc^i)<<4), x[i].x,x[i].y,x[i].z,x[i].w);
  #pragma unroll
  for(int i=0;i<4;i++) lds128(sb+OFF_XAE+tw*128+((i^pq)<<4), st[i].x,st[i].y,st[i].z,st[i].w);
  const uint32_t ep = lds32(sb+OFF_MISC);
  for(int n=0;n<2000000;n++){
    if(!((st[0].w^ep)|(st[1].w^ep)|(st[2].w^ep)|(st[3].w^ep)) && x[0].x && x[1].x) break;
    const uint32_t t2=tid_now()&127;
    #pragma unroll
    for(int i=0;i<2;i++) ld_rlx128(&g_xa[cb*1024+t2*8+(pc^i)], x[i]);
    #pragma unroll
    for(int i=0;i<4;i++) ld_rlx128(&g_qs[t2*8+(i^pq)], st[i]);
  }
  __syncwarp();
#define LNA(X,S) ({ const uint32_t d_=hsub2_bf16(X,S.x); hfma2_bf16(d_,S.y,hmul2_bf16(d_,S.z)); })
  #pragma unroll
  for(int i=0;i<2;i++){
    x[i].x=~x[i].x;
    a[i].x=LNA(x[i].x,st[0]); a[i].y=LNA(x[i].y,st[1]); a[i].z=LNA(x[i].z,st[2]); a[i].w=LNA(x[i].w,st[3]);
  }
}
template<int PART> __device__ __forceinline__ void conv_put(const float* a0, const float* a1, uint32_t sb, int warp, int lane){
  const uint32_t eb = sb + (PART? OFF_IMG+warp*4096 : OFF_TBL+(warp>>2)*2*TBL+(warp&3)*4096), x8 = sb+OFF_X8+warp*512;
  const uint32_t rho = (lane&24)|((lane&3)<<1)|((lane>>2)&1);
  #pragma unroll
  for(int ii=0;ii<8;ii++){
    const uint32_t w0=pack_bf16(a0[4*ii],a0[4*ii+1]), w1=pack_bf16(a0[4*ii+2],a0[4*ii+3]), w2=pack_bf16(a1[4*ii],a1[4*ii+1]), w3=pack_bf16(a1[4*ii+2],a1[4*ii+3]);
    sts128(eb+rho*128+(((rho+ii)&7)<<4), w0,w1,w2,w3);
    if(PART && ii==0) sts128(x8+rho*16, w0,w1,w2,w3);
  }
  __syncwarp();
}
template<int PART> __device__ __forceinline__ void conv_get(const uint4* x, const uint4* a, uint32_t sb, int warp, int lane){
  const int cb = CGMAP(blockIdx.x>>1)*2+(blockIdx.x&1), chl = (warp>>2)*2;
  const uint32_t tw = (warp&3)*32+lane;
  const uint32_t eb = sb + (PART? OFF_IMG+warp*4096 : OFF_TBL+(warp>>2)*2*TBL+(warp&3)*4096), x8 = sb+OFF_X8+warp*512;
  uint4 d[4][2];
  #pragma unroll
  for(int c=0;c<4;c++){
    const uint32_t tc = (lane>>3)+c, rho = c*8+((tc&3)<<1)+(lane&1), sl = (lane&6)+(tc>>2);
    lds128(eb+rho*128+(((rho+sl)&7)<<4), d[c][0].x,d[c][0].y,d[c][0].z,d[c][0].w);
    uint32_t ad = eb+rho*128+(((rho+sl+1)&7)<<4);
    if(c>0 && sl==7) ad = PART? sb+OFF_U+128*16 : x8+rho*16;
    lds128(ad, d[c][1].x,d[c][1].y,d[c][1].z,d[c][1].w);
  }
#define SUM4(K,F) hadd2_bf16(hadd2_bf16(d[0][K].F,d[1][K].F),hadd2_bf16(d[2][K].F,d[3][K].F))
  uint4 o0, o1;
  o0.x=hadd2_bf16(x[0].x,hmul2_bf16(a[0].x,SUM4(0,x))); o0.y=hadd2_bf16(x[0].y,hmul2_bf16(a[0].y,SUM4(0,y)));
  o0.z=hadd2_bf16(x[0].z,hmul2_bf16(a[0].z,SUM4(1,x))); o0.w=hadd2_bf16(x[0].w,hmul2_bf16(a[0].w,SUM4(1,y)));
  o1.x=hadd2_bf16(x[1].x,hmul2_bf16(a[1].x,SUM4(0,z))); o1.y=hadd2_bf16(x[1].y,hmul2_bf16(a[1].y,SUM4(0,w)));
  o1.z=hadd2_bf16(x[1].z,hmul2_bf16(a[1].z,SUM4(1,z))); o1.w=hadd2_bf16(x[1].w,hmul2_bf16(a[1].w,SUM4(1,w)));
  uint4* dst = (uint4*)(g_hT + (cb*4+chl)*2048 + (1-PART)*1024) + tw;
  dst[0]=o0; dst[256]=o1;
}

__global__ void __cluster_dims__(2,1,1) __launch_bounds__(384,1)
fused_kernel(const __grid_constant__ Maps maps, const bf16* __restrict__ q, const bf16* __restrict__ shk, const bf16* __restrict__ ssmk,
             const bf16* __restrict__ ssmD, const bf16* __restrict__ wgt, const bf16* __restrict__ wup, const bf16* __restrict__ wdn, bf16* __restrict__ out){
  extern __shared__ __align__(1024) uint8_t smem_raw[];
  unsigned c_begin; asm volatile("mov.u32 %0, %%clock;":"=r"(c_begin));
  const uint32_t sb = smem_u32(smem_raw);
  const int tid = threadIdx.x, lane = tid&31;
  const int warp = __shfl_sync(0xffffffffu, tid>>5, 0);
  const int wg = warp>>2;
  const int b = blockIdx.x, rank = b&1;
  const int f = b&7, rt = b>>3, fp = f>>1;
  const uint32_t bar = sb+OFF_BAR;

  if(wg==2){
    asm volatile("setmaxnreg.dec.sync.aligned.u32 " STR(RP) ";");
    STAMP(58);
    const int cg = CGMAP(b>>1);
    const int cb = cg*2+rank;
    auto ldkv=[&](int i){
      const uint32_t fb=bar+8*(B_KV+i);
      mbar_expect_tx(fb, 2176+2048);
      tma3d(sb+KVOFF(i),      &maps.k, cg*8, i*32+rank*16-1, 0, fb);
      tma3d(sb+KVOFF(i)+2176, &maps.v, cg*8, i*32+rank*16,   0, fb);
    };
    if(warp==9){ if(lane<3) asm volatile("prefetch.tensormap [%0];"::"l"(&maps.k+lane):"memory"); }
    STAMP(51+warp);
    asm volatile("bar.sync 0;":::"memory");
    asm volatile("barrier.cluster.arrive.relaxed.aligned;":::"memory");
    unsigned epoch = 0;
    if(warp>=10) epoch = (*(volatile unsigned*)&g_cnt[warp==10? 64:32] >> 7) + 1;
    uint4 shw = make_uint4(0,0,0,0); uint2 dd = make_uint2(0,0);
    if(warp!=9){ shw = *(const uint4*)(shk + (cg*8+(lane&3)*2)*4); dd = *(const uint2*)(ssmD + cb*4); }
    if(warp==9){
      { unsigned c1; do{ asm volatile("mov.u32 %0, %%clock;":"=r"(c1)); }while(c1-c_begin<QDELAY); }
      if(elect_one()){
        mbar_expect_tx(bar+8*B_SK, 16384);
        bulk_g2s(sb+OFF_SK, ssmk+cb*4*2048, 16384, bar+8*B_SK);
        #pragma unroll
        for(int i=0;i<KV0;i++) ldkv(i);
      }
      __syncwarp();
      mbar_wait(bar+8*B_QD, 0);
      STAMP(79);
      if(elect_one()){
        asm volatile("cp.async.bulk.tensor.2d.global.shared::cta.bulk_group [%0, {%1, %2}], [%3];"::"l"(&maps.xa),"r"(b*64),"r"(0),"r"(sb+OFF_IMG):"memory");
        asm volatile("cp.async.bulk.commit_group;":::"memory");
        #pragma unroll 1
        for(int i=KV0;i<8;i++) ldkv(i);
        asm volatile("cp.async.bulk.wait_group.read 0;":::"memory");
        mbar_arrive(bar+8*(B_XA+1));
        mbar_wait(bar+8*(B_KV+XPOS), 0);
        mbar_expect_tx(bar+8*B_XA, 32768); bulk_g2s(sb+OFF_XAL, &g_xa[cb*1024], 16384, bar+8*B_XA); bulk_g2s(sb+OFF_XAE, g_qs, 16384, bar+8*B_XA);
        STAMP(66);
        mbar_wait(bar+8*(B_KV+WSTART), 0);
        #pragma unroll 1
        for(int it=0;it<3;it++){
          mbar_wait(bar+8*(B_WEMPTY+it), 0);
          mbar_expect_tx(bar+8*(B_WFULL+it), 22528);
          load_w_stage(maps, sb+OFF_W+(5-it)*WSLOT, f*FS, ((it+(rt&14))&15)*32, bar+8*(B_WFULL+it));
          STAMP(24+it);
        }
      }
      __syncwarp();
    }
    if(warp==11){
      if(lane<4) sts128(sb+OFF_ROW+lane*16, __byte_perm(shw.x,shw.z,0x5410), __byte_perm(shw.x,shw.z,0x7632), __byte_perm(shw.y,shw.w,0x5410), __byte_perm(shw.y,shw.w,0x7632));
      if(lane==0) sts128(sb+OFF_MISC, epoch, dd.x, dd.y, 0);
      __syncwarp();
      if(lane==0) mbar_arrive(bar+8*B_SC);
    }
    if(warp==8 && lane<7) asm volatile("prefetch.tensormap [%0];"::"l"(&maps.wg64+lane):"memory");
    if(warp==9){ mbar_wait(bar+8*B_SC, 0); epoch = lds32(sb+OFF_MISC); }
    const uint32_t par = epoch&1;
    auto ldx=[&](int w, int it){
      const uint32_t fb = bar+8*(B_XFULL+w*NX+(it&3));
      mbar_expect_tx(fb, XSLOT);
      tma2d_mc(sb+OFF_X+(w*NX+(it&3))*XSLOT+rank*4096, &maps.ht, w*1024+rt*64, ((it+(rt>>1)+w*(SKW/2))&7)*64+rank*32, fb);
    };
    if(warp!=9){
      const int cp = lane&3;
      uint32_t sw[4];
      { const uint4 w = shw;
        sw[0]=__byte_perm(w.x,w.z,0x5410); sw[1]=__byte_perm(w.x,w.z,0x7632); sw[2]=__byte_perm(w.y,w.w,0x5410); sw[3]=__byte_perm(w.y,w.w,0x7632); }
      const uint32_t udst = mapa(sb+OFF_U+(cp&1)*2*UCH, cp>>1), ubar = mapa(bar+8*B_U, cp>>1);
      asm volatile("barrier.cluster.wait.aligned;":::"memory");
      #pragma unroll 1
      for(int tk=2*CP+(warp==8? 2:warp-10); tk<16; tk+=3){
        const int T=tk>>1, gl=(tk&1)*8+(lane>>2);
        mbar_wait(bar+8*(B_KV+T), 0);
        if(!(tk&1)) STAMP(8+T);
        const uint32_t ka = sb+KVOFF(T)+gl*16+cp*4, va = ka+2176;
        uint32_t kk[11], u[8];
        #pragma unroll
        for(int r=0;r<3;r++) kk[r]=lds32(ka+(5+r)*272);
        #pragma unroll
        for(int r=0;r<8;r++){ kk[3+r]=lds32(ka+16+r*272); u[r]=lds32(va+r*256); }
        #pragma unroll
        for(int r=0;r<8;r++){
          uint32_t a=hmul2_bf16(kk[r],sw[3]); a=hadd2_bf16(a,hmul2_bf16(kk[r+1],sw[2])); a=hadd2_bf16(a,hmul2_bf16(kk[r+2],sw[1])); a=hadd2_bf16(a,hmul2_bf16(kk[r+3],sw[0]));
          u[r]=hmul2_bf16(a,u[r]);
        }
        const int R = 255-(T*32+rank*16+gl);
        const uint32_t d = udst + (R&1)*UPL + (R>>1)*16;
        st_async128(d,     __byte_perm(u[7],u[6],0x5410), __byte_perm(u[5],u[4],0x5410), __byte_perm(u[3],u[2],0x5410), __byte_perm(u[1],u[0],0x5410), ubar+8*T);
        st_async128(d+UCH, __byte_perm(u[7],u[6],0x7632), __byte_perm(u[5],u[4],0x7632), __byte_perm(u[3],u[2],0x7632), __byte_perm(u[1],u[0],0x7632), ubar+8*T);
      }
      __syncwarp();
      if(lane==0) mbar_arrive(bar+8*B_TD);
    } else {
      asm volatile("barrier.cluster.wait.aligned;":::"memory");
    }
    if(warp==8){
      int slot=3, ph=0;
      #pragma unroll 1
      for(int it=3; it<24+SKW; it++){
        mbar_wait(bar+8*(B_WEMPTY+slot), ph);
        if(it==3) mbar_wait(bar+8*B_TD, 0);
        if(it==6) mbar_wait(bar+8*B_PK, 0);
        if(it>=PACE && it<NS) mbar_wait(bar+8*(B_WFULL+it-PACE), 0);
        if(elect_one()){
          const uint32_t fb = bar+8*(B_WFULL+slot), dst = sb+OFF_W+(5-slot)*WSLOT;
          mbar_expect_tx(fb, 22528);
          if(it<16+SKW) load_w_stage(maps, dst, f*FS, ((it+(rt&14))&15)*32, fb);
          else {
            const int j = it-16-SKW, ci = (G2_CH >> (4*j)) & 3, kh = ((G2_PEER >> j) & 1) ^ rank;
            tma2d(dst, &maps.wd, rank*256+((fp+ci)&3)*64, (2*fp+kh)*FS, fb);
          }
        }
        __syncwarp();
        if(it==WDPF && elect_one()) asm volatile("cp.async.bulk.prefetch.L2.global [%0], 11008;"::"l"(wdn+b*5504):"memory");
        __syncwarp();
        #pragma unroll
        for(int w=0;w<2;w++){
          const int i2 = it-w*SKW;
          if((i2&1) && i2>=7 && i2<15){ const int j=(i2+1)>>1; mbar_wait(bar+8*(B_XEMPTY+w*NX+(j&3)), 0); if(elect_one()) ldx(w,j); __syncwarp(); }
        }
        if(it==5){ mbar_wait(bar+8*B_X03, 0); if(elect_one()) ldx(0,3); __syncwarp(); }
        if(++slot==NS){ slot=0; ph^=1; }
      }
    } else if(warp==11){
      #pragma unroll 4
      for(int i=0;i<32;i++) ((uint4*)out)[b*1024+i*32+lane]=make_uint4(0,0,0,0);
      asm volatile("fence.proxy.async.global;":::"memory");
      __syncwarp();
      if(lane==0) mbar_arrive(bar+8*(B_HD+1));
      STAMP(30);
      mbar_wait(bar+8*(B_RES+1), 0);
      STAMP(31);
      {
        const int j = rt*6+(lane>>2);
        float4 c = make_float4(0.f,0.f,0.f,0.f);
        if(lane<24 && j<88) c = gather_sum(&g_csp[(f*16+(lane&3)*4)*88+j], 4, 88, par);
        __syncwarp();
        #pragma unroll
        for(int o=1;o<4;o<<=1){ c.x+=__shfl_xor_sync(~0u,c.x,o); c.y+=__shfl_xor_sync(~0u,c.y,o); c.z+=__shfl_xor_sync(~0u,c.z,o); c.w+=__shfl_xor_sync(~0u,c.w,o); }
        if(lane<24 && j<88 && !(lane&3)) st_rlx128(&g_cs2[f*96+j], (__float_as_uint(c.x)&~1u)|par, __float_as_uint(c.y), __float_as_uint(c.z), __float_as_uint(c.w));
      }
      STAMP(29);
      { uint4 v[3]; int n=0; const int j2 = lane<24? lane+64 : lane;
        do{ __nanosleep(CSLEEP); ld_rlx128(&g_cs2[f*96+lane], v[0]); ld_rlx128(&g_cs2[f*96+lane+32], v[1]); ld_rlx128(&g_cs2[f*96+j2], v[2]); spin_guard(++n); }while(((v[0].x^par)|(v[1].x^par)|(v[2].x^par))&1);
        *(uint4*)(smem_raw+OFF_CS+lane*16)=v[0]; *(uint4*)(smem_raw+OFF_CS+(lane+32)*16)=v[1]; *(uint4*)(smem_raw+OFF_CS+j2*16)=v[2]; }
      __syncwarp();
      if(lane<2) mbar_arrive(bar+8*(B_PAR+lane));
      STAMP(74);
      #pragma unroll 4
      for(int i=0;i<32;i++) g_xa[cb*1024+i*32+lane]=make_uint4(0,0,0,0);
    } else {
      const int w = warp-9;
      const uint32_t rbase = sb+(w? OFF_RES1:OFF_RES0);
      mbar_wait(bar+8*(B_HD+w), 0);
      STAMP(67+w*3);
      if(elect_one()){
        signal_add(&g_cnt[32+32*w]); STAMP(68+w*3);
        const uint32_t xf = bar+8*(B_XFULL+w*NX), xd = sb+OFF_X+w*NX*XSLOT+rank*4096;
        const int c0 = w*1024+rt*64, k0 = (rt>>1)+w*(SKW/2);
        mbar_expect_tx(xf, XSLOT); mbar_expect_tx(xf+8, XSLOT); mbar_expect_tx(xf+16, XSLOT); mbar_expect_tx(bar+8*(B_RES+w), XSLOT);
        unsigned v; int n=0; do{ asm volatile("ld.acquire.gpu.global.u32 %0, [%1];":"=r"(v):"l"(&g_cnt[32+32*w]):"memory"); spin_guard(++n); }while((int)(v-epoch*128)<0);
        STAMP(7+w*16);
        asm volatile("fence.proxy.async.global;":::"memory");
        tma2d_mc(xd,         &maps.ht, c0, (k0&7)*64+rank*32,     xf);
        tma2d_mc(xd+XSLOT,   &maps.ht, c0, ((k0+1)&7)*64+rank*32, xf+8);
        tma2d_mc(xd+2*XSLOT, &maps.ht, c0, ((k0+2)&7)*64+rank*32, xf+16);
        tma2d(rbase,      &maps.ht, c0, rank*256+fp*64,    bar+8*(B_RES+w));
        tma2d(rbase+4096, &maps.ht, c0, rank*256+fp*64+32, bar+8*(B_RES+w));
        if(!w) mbar_arrive(bar+8*B_X03);
        if(w) ldx(1,3);
      }
      __syncwarp();
      STAMP(69+w*3);
      mbar_wait(bar+8*(B_RES+w), 0);
      {
        float s0=0.f,s1=0.f,q0=0.f,q1=0.f;
        #pragma unroll 8
        for(int k=0;k<64;k++){
          const uint32_t v=lds32(rbase + k*128 + ((((lane>>2)^(k&7))<<4)|((lane&3)<<2)));
          const float a=bf_lo(v), bb=bf_hi(v); s0+=a; q0=fmaf(a,a,q0); s1+=bb; q1=fmaf(bb,bb,q1);
        }
        st_rlx128(&g_stat[((rt*2+w)*8+f)*32+lane], (__float_as_uint(s0)&~1u)|par, __float_as_uint(q0), __float_as_uint(s1), __float_as_uint(q1));
      }
      {
        __nanosleep(CSLEEP);
        const float4 st=gather_sum(&g_stat[((rt*2+w)*8)*32+lane], 8, 32, par);
        const float s0=st.x, q0=st.y, s1=st.z, q1=st.w;
        const float m0=s0*(1.f/512), m1=s1*(1.f/512);
        const float v0=fmaxf(q0*(1.f/512)-m0*m0,0.f), v1=fmaxf(q1*(1.f/512)-m1*m1,0.f);
        const float r0=ln_rstd(v0), r1=ln_rstd(v1);
        *(float4*)(smem_raw+OFF_ROW+w*512+lane*16)=make_float4(-rbf(m0),r0,-rbf(m1),r1);
        __syncwarp();
        if(lane==0) mbar_arrive(bar+8*(B_PAR+w));
        STAMP(75+w);
      }
      STAMP(77+w);
    }
  } else {
    if(elect_one()){
      mbar_init(bar+8*(B_Q+warp),1);
      asm volatile("fence.proxy.async.shared::cta;":::"memory");
      mbar_expect_tx(bar+8*(B_Q+warp), 2048);
      const bf16* qp = q + pos2row((1-wg)*1024+b*8+(warp&3)*2)*512;
      bulk_g2s(sb+OFF_Q+2*warp*QP, qp, 1024, bar+8*(B_Q+warp)); bulk_g2s(sb+OFF_Q+(2*warp+1)*QP, qp-16*512, 1024, bar+8*(B_Q+warp));
    }
    __syncwarp();
    asm volatile("setmaxnreg.inc.sync.aligned.u32 " STR(RC) ";");
    if(elect_one()){
      mbar_init(bar+8*(B_U+warp),1); mbar_expect_tx(bar+8*(B_U+warp), 2048);
      mbar_init(bar+8*(B_XFULL+warp),1); mbar_init(bar+8*(B_XEMPTY+warp),8);
      mbar_init(bar+8*(B_KV+warp),1);
      if(warp<NS){ mbar_init(bar+8*(B_WFULL+warp),1); mbar_init(bar+8*(B_WEMPTY+warp),8); mbar_init(bar+8*(B_ONE+warp),1); }
      else { const int i=warp-6; mbar_init(bar+8*(B_PRDY+i),4); mbar_init(bar+8*(B_AFULL+i),1); mbar_expect_tx(bar+8*(B_AFULL+i), 22528); mbar_init(bar+8*(B_PAR+i),2); mbar_init(bar+8*(B_HD+i),8+i); if(i){ mbar_init(bar+8*B_SK,1); mbar_init(bar+8*B_SC,1); mbar_init(bar+8*B_X03,9); } else { mbar_init(bar+8*B_QD,8); mbar_init(bar+8*B_PK,3); mbar_init(bar+8*B_TD,3); } }
      asm volatile("fence.mbarrier_init.release.cluster;":::"memory");
    }
    __syncwarp();
    STAMP(56);
    const int wq = warp&3, g = lane>>2, t = lane&3;
    if(tid<8){ sts128(sb+OFF_U+tid*UPL+128*16, 0,0,0,0); }
    if(tid<12){ sts128(sb+OFF_TBL+(tid&3)*TBL+(tid>>2)*16, 0,0,0,0); }
    asm volatile("bar.sync 0;":::"memory");
    asm volatile("barrier.cluster.arrive.relaxed.aligned;":::"memory");
    STAMP(57);
    #pragma unroll
    for(int i=0;i<4;i++) mbar_wait(bar+8*(B_Q+wg*4+i), 0);
    STAMP(92+wg);
    {
      const uint32_t la = sb+OFF_Q+(wg*8+2*(lane>>3)+(lane&1))*QP + ((lane&7)>>1)*16 + wq*256;
      uint4 tv[4]; uint32_t w[2][8];
      const int irow = wq*32+t*2+(g>>2);
      const uint32_t dst = sb+OFF_IMG+irow*128+(((((g&3)+4*wg)^(b&7))^(irow&7))<<4);
      #pragma unroll
      for(int i=0;i<4;i++) ldsm4t(la+i*64, tv[i].x,tv[i].y,tv[i].z,tv[i].w);
      #pragma unroll
      for(int i=0;i<4;i++) sts128(dst+i*1024, max(~tv[i].x,1u),tv[i].y,tv[i].z,tv[i].w);
      asm volatile("fence.proxy.async.shared::cta;":::"memory");
      __syncwarp();
      if(lane==0) mbar_arrive(bar+8*B_QD);
      if(wg==0) STAMP(44);
      const uint32_t qa = sb+OFF_Q+(2*warp)*QP+lane*16;
      #pragma unroll
      for(int r=0;r<2;r++){ lds128_nm(qa+r*QP, w[r][0],w[r][1],w[r][2],w[r][3]); lds128_nm(qa+r*QP+512, w[r][4],w[r][5],w[r][6],w[r][7]); }
      float s[2], d[2];
      #pragma unroll
      for(int r=0;r<2;r++){
        float s0=0.f,s1=0.f,d0=0.f,d1=0.f;
        #pragma unroll
        for(int i=0;i<8;i++){ const float lo=bf_lo(w[r][i]), hi=bf_hi(w[r][i]); s0+=lo; s1+=hi; d0=fmaf(lo,lo,d0); d1=fmaf(hi,hi,d1); }
        s[r]=s0+s1; d[r]=d0+d1;
      }
      const bool u=lane&16, v=lane&8;
      const float a0=(u? s[1]:s[0])+__shfl_xor_sync(~0u,u? s[0]:s[1],16), a1=(u? d[1]:d[0])+__shfl_xor_sync(~0u,u? d[0]:d[1],16);
      float c0=(v? a1:a0)+__shfl_xor_sync(~0u,v? a0:a1,8);
      c0+=__shfl_xor_sync(~0u,c0,4); c0+=__shfl_xor_sync(~0u,c0,2); c0+=__shfl_xor_sync(~0u,c0,1);
      const float m=c0*(1.f/512), sq=__shfl_down_sync(~0u,c0,8);
      const float rs=ln_rstd(fmaxf(fmaf(-m,m,sq*(1.f/512)),0.f)), rh=rbf(rs);
      const float m1=__shfl_down_sync(~0u,m,16), rs1=__shfl_down_sync(~0u,rs,16), rh1=rbf(rs1);
      mbar_wait(bar+8*B_SC, 0);
      if(lane==0){ st_rlx128(&g_qs[b*8+(warp^(b&7))], pack_bf16(m,m1), pack_bf16(rh,rh1), pack_bf16(rs-rh,rs1-rh1), lds32(sb+OFF_MISC)); }
      __syncwarp();
      if(wg==0) STAMP(46);
    }
    mbar_wait(bar+8*B_SK, 0);
    STAMP(90+wg);
    {
      const int Q = tid+2;
      const uint32_t ta = sb+OFF_TBL+((Q*32)^(((Q>>2)&3)<<5));
      const bool sw2 = (Q>>2)&1;
      uint4 kq[4]; uint32_t kn[4];
      #pragma unroll
      for(int i=0;i<4;i++){ lds128_nm(sb+OFF_SK+i*4096+tid*16, kq[i].x,kq[i].y,kq[i].z,kq[i].w); kn[i] = lds32(sb+OFF_SK+i*4096+(warp+1)*512); }
      if(tid==0){
        const uint32_t d01=lds32(sb+OFF_MISC+4), d23=lds32(sb+OFF_MISC+8);
        kq[0].x=hadd2_bf16(kq[0].x,d01&0xffffu); kq[1].x=hadd2_bf16(kq[1].x,d01>>16); kq[2].x=hadd2_bf16(kq[2].x,d23&0xffffu); kq[3].x=hadd2_bf16(kq[3].x,d23>>16);
      }
      __syncwarp();
      #pragma unroll
      for(int i=0;i<4;i++){
        uint32_t nx = __shfl_down_sync(~0u, kq[i].x, 1); if(lane==31) nx = kn[i];
        const uint4 o = make_uint4(__byte_perm(kq[i].x,kq[i].y,0x5432), __byte_perm(kq[i].y,kq[i].z,0x5432), __byte_perm(kq[i].z,kq[i].w,0x5432), __byte_perm(kq[i].w,nx,0x5432));
        const uint4 f0 = sw2? o:kq[i], f1 = sw2? kq[i]:o;
        sts128(ta+i*TBL+(sw2?16:0), f0.x,f0.y,f0.z,f0.w);
        sts128(ta+i*TBL+(sw2?0:16), f1.x,f1.y,f1.z,f1.w);
        if(tid==0) sts128(sb+OFF_TBL+i*TBL+48, 0,0,0, kq[i].x<<16);
      }
      __syncwarp();
      if(lane<4 && lane!=2) mbar_arrive(bar+8*(B_WEMPTY+lane));
      asm volatile("bar.sync 1, 256;":::"memory");
    }
    STAMP(80+wg);
    STAMP(82+wg);
    asm volatile("barrier.cluster.wait.aligned;":::"memory");
    {
      const int c=lane>>3, p=g&1;
      uint32_t tb[5];
      #pragma unroll
      for(int s=0;s<5;s++){ const int y=16*c+wq+t+p+4*s; const int id=8*(y>>2)+4*(1-p)+(y&3); tb[s]=sb+OFF_TBL+wg*2*TBL+((id^(((id>>5)&3)<<3))<<2); }
      uint64_t du = make_desc(sb+OFF_U+wg*2*UCH, UPL, 128, 0);
      float aE[2][32], aL[2][32];
      uint32_t R[2][4][8]; uint4 xr[2], ar[2];
#define P_TY(K) ((K)>=8 ? 2 : (K)&1)
#define P_LV(K) ((K)>=8 ? (K)-8 : (K)>>1)
#define P_MA(K) ((P_TY(K)==1 ? 15 : 7) - 2*P_LV(K))
#define P_N(K,M) (P_TY(K)==2 ? 64 : P_TY(K)==1 ? 128-8*(M) : 64-8*(M))
#define P_B(K,M) (8*(M) + (P_TY(K)==0 ? 64 : 0))
#define P_LD(K,J) conv_lda(R[(K)&1][J],tb,((J)&1)*TBL+(P_MA(K)-((J)>>1))*512)
#define P_MMA(K,J) conv_mma<P_N(K,P_MA(K)-((J)>>1))>(P_TY(K)==0? aE[(J)&1]:aL[(J)&1], R[(K)&1][J], du+((J)&1)*(UCH/16)+P_B(K,P_MA(K)-((J)>>1)))
      const uint32_t kva = sb+OFF_KV+(warp*2+p)*16+t*4, udst = mapa(sb+OFF_U+((t&1)*2+(c&1))*UCH, t>>1), ubar = mapa(bar+8*B_U, t>>1);
      uint32_t ko[5];
      #pragma unroll
      for(int r=0;r<5;r++){ const int row=2*c-3+r; ko[r]=kva+(row&7)*272+(row<0?0:16); }
#define KV_PREP(T) if constexpr(T<CP){ mbar_wait(bar+8*(B_KV+T),0); if(wg==0) STAMP(8+T); uint32_t k_[5], w0,w1,w2,w3; lds128_nm(sb+OFF_ROW+t*16, w0,w1,w2,w3); \
        _Pragma("unroll") for(int r=0;r<5;r++) k_[r]=lds32(ko[r]+T*KVCH); \
        uint32_t u0=lds32(kva+T*KVCH+2176+c*512), u1=lds32(kva+T*KVCH+2176+c*512+256); \
        u0=hmul2_bf16(hadd2_bf16(hadd2_bf16(hadd2_bf16(hmul2_bf16(k_[0],w3),hmul2_bf16(k_[1],w2)),hmul2_bf16(k_[2],w1)),hmul2_bf16(k_[3],w0)),u0); \
        u1=hmul2_bf16(hadd2_bf16(hadd2_bf16(hadd2_bf16(hmul2_bf16(k_[1],w3),hmul2_bf16(k_[2],w2)),hmul2_bf16(k_[3],w1)),hmul2_bf16(k_[4],w0)),u1); \
        const uint32_t kp_=__byte_perm(u1,u0,(c&1)?0x7632:0x5410), rc_=__shfl_xor_sync(~0u,__byte_perm(u1,u0,(c&1)?0x5410:0x7632),8); \
        const uint32_t lo_=(c&1)? rc_:kp_, hi_=(c&1)? kp_:rc_;     \
        const uint32_t l2_=__shfl_xor_sync(~0u,lo_,16), h2_=__shfl_xor_sync(~0u,hi_,16); \
        const int R_=255-(T*32+rank*16+warp*2+p); \
        if(c<2) st_async128(udst+(R_&1)*UPL+(R_>>1)*16, h2_, l2_, hi_, lo_, ubar+8*T); }
#define CONV_PREP(K) { P_LD(K,0); P_LD(K,1); P_LD(K,2); P_LD(K,3); }
#define CONV_PAIR(K) { \
        _Pragma("unroll") for(int j=0;j<4;j++) conv_dup(R[(K)&1][j]); \
        if constexpr(P_TY(K)<2){ _Pragma("unroll") for(int i=0;i<2;i++){ float* a_=(P_TY(K)==0? aE[i]:aL[i])+8*P_LV(K); zero4(a_); zero4(a_+4); } } \
        if constexpr(P_TY(K)!=1){ mbar_wait(bar+8*(B_U+P_LV(K)+(P_TY(K)?4:0)),0); if constexpr(P_TY(K)==2 || PFE) asm volatile("fence.proxy.async.shared::cta;":::"memory"); } \
        asm volatile("" : "+l"(du)); \
        PP_SYNC(); \
        STAMP(96+wg*16+(K)); \
        wg_fence(); \
        P_MMA(K,0); P_MMA(K,1); \
        if constexpr(P_TY(K)<2){ wg_commit(); wg_fence(); } \
        P_MMA(K,2); P_MMA(K,3); \
        wg_commit(); \
        if((K)<11 || wg==0) PP_ARRIVE(); \
        if constexpr((K)<11){ if constexpr((K)>0){ if constexpr(P_TY(K)<2) wg_wait<2>(); else wg_wait<1>(); } if constexpr((K)!=KEPI || (K)==6) CONV_PREP((K)+1) } }
#define PP_SYNC() asm volatile("bar.sync %0, 256;"::"r"(2+wg):"memory")
#define PP_ARRIVE() asm volatile("bar.arrive %0, 256;"::"r"(3-wg):"memory")
      if(wg==1) PP_ARRIVE();
      KV_PREP(0) CONV_PREP(0) KV_PREP(1) CONV_PAIR(0) CONV_PAIR(1) KV_PREP(2) CONV_PAIR(2) CONV_PAIR(3) KV_PREP(3) CONV_PAIR(4) CONV_PAIR(5) CONV_PAIR(6)
      if(lane==0) mbar_arrive(bar+8*(B_WEMPTY+2));
#define CONV_EPIE(K) if constexpr((K)==KEPI){ mbar_wait(bar+8*B_XA,0); load_xa<1>(xr,ar,sb,warp,lane); if constexpr((K)==6) wg_wait<0>(); conv_put<1>(aE[0],aE[1],sb,warp,lane); \
        conv_get<1>(xr,ar,sb,warp,lane); __syncwarp(); if(lane==0) mbar_arrive(bar+8*B_HD); STAMP(84+wg); if constexpr((K)!=6) CONV_PREP((K)+1) } \
      if constexpr((K)==KEPI+1){ load_xa<0>(xr,ar,sb,warp,lane); if(lane==0) mbar_arrive(bar+8*(B_WEMPTY+4)); }
      CONV_EPIE(6)
      CONV_PAIR(7) CONV_EPIE(7)
      CONV_PAIR(8) CONV_EPIE(8)
      CONV_PAIR(9) CONV_EPIE(9)
      CONV_PAIR(10)
      CONV_PAIR(11)
      wg_wait<0>();
      STAMP(86+wg);
      conv_put<0>(aL[0],aL[1],sb,warp,lane);
      conv_get<0>(xr,ar,sb,warp,lane);
      __syncwarp();
      if(lane==0){ mbar_arrive(bar+8*(B_HD+1)); mbar_arrive(bar+8*(B_WEMPTY+5)); }
      if(wg==0 && lane<2) mbar_arrive_cl(mapa(bar+8*B_X03, lane));
      STAMP(88+wg);
    }
    if(wg==1 && wq<3){
      mbar_wait(bar+8*(B_WFULL+(rt&1)), 0);
      const int j = tid-128;
      const uint32_t par = lds32(sb+OFF_MISC)&1;
      float c0=0.f,c1=0.f,c2=0.f,c3=0.f;
      const uint32_t cb = sb+OFF_W+(5-(rt&1))*WSLOT+wq*4096+t*4;
      #pragma unroll 8
      for(int k=0;k<32;k++){
        const uint32_t ad = cb + k*128 + ((g^(k&7))<<4);
        const uint32_t v=lds32(ad), u=lds32(ad+12288); c0+=bf_lo(v); c1+=bf_hi(v); c2+=bf_lo(u); c3+=bf_hi(u);
      }
      if(j<88) st_rlx128(&g_csp[(f*16+rt)*88+j], (__float_as_uint(c0)&~1u)|par, __float_as_uint(c1), __float_as_uint(c2), __float_as_uint(c3));
      __syncwarp();
      if(lane==0) mbar_arrive(bar+8*B_PK);
    }
    const uint32_t xempty_cl = mapa(bar+8*(B_XEMPTY+wg*NX), lane&1);
    float ag[88], au[88];
    const uint32_t xbase = sb+OFF_X+wg*NX*XSLOT;
    constexpr uint64_t DHI_A = (uint64_t)0x40000040u<<32, DHI_B = DHI_A | (256u<<16);
    uint32_t wb = bar+8*wg*(SKW%NS), ph = wg*(SKW/NS), dbl = (((sb+OFF_W+(5-wg*(SKW%NS))*WSLOT)&0x3FFFF)>>4), dal = (xbase&0x3FFFF)>>4, xb = bar+8*(B_XFULL+wg*NX), pwb = 0;
    uint32_t relm = lane==0? 0xff : lane==1? (wg? (0xff00>>(SKW/2))&0xff : (1<<(SKW/2))-1) : 0;
#define G1_STAGE(DA,DB,ACC) { wg_fence(); wgmma_ss<176,1,1>(ag, DA, DB, ACC); wgmma_ss<176,1,1>(au, DA, (DB)+768, ACC); wgmma_ss<176,1,1>(ag, (DA)+128, (DB)+128, 1); wgmma_ss<176,1,1>(au, (DA)+128, (DB)+768+128, 1); wg_commit(); }
    {
      mbar_wait(xb, 0);
      if(SKW>=NS) mbar_wait(wb, 0);
      mbar_wait(wb, ph);
      STAMP(1+wg*16);
      #pragma unroll
      for(int i=0;i<88;i++){ ag[i]=0.f; au[i]=0.f; }
      G1_STAGE(DHI_A|dal, DHI_B|dbl, 0)
    }
    #pragma unroll 1
    for(int xi=0; xi<8; xi++){
      mbar_wait(wb+8, ph);
      G1_STAGE(DHI_A|(dal+256), DHI_B|(dbl-WSLOT/16), 1)
      pwb = wb;
      const bool wrap = wb==bar+8*4;
      wb = wrap? bar : wb+16; dbl = wrap? dbl+4*(WSLOT/16) : dbl-2*(WSLOT/16); ph ^= wrap;
      dal = (xi==3)? dal-3*512 : dal+512; xb = (xi==3)? xb-24 : xb+8;
      uint32_t rel = relm&1; relm>>=1; uint32_t xpar = xi>=3;
      asm volatile("":"+r"(rel),"+r"(xpar));
      wg_wait<1>();
      if(rel) mbar_arrive(pwb+8*B_WEMPTY);
      if(xi==7) break;
      mbar_wait(xb, xpar);
      mbar_wait(wb, ph);
      G1_STAGE(DHI_A|dal, DHI_B|dbl, 1)
      wg_wait<1>();
      if(rel) mbar_arrive(pwb+8*B_WEMPTY+8);
      if((lane>>1)==1) mbar_arrive_cl(xempty_cl+8*(xi&3));
    }
    mbar_wait(bar+8*(B_PAR+wg), 0);
    const float2 p0=*(const float2*)(smem_raw+OFF_ROW+(wg*64+wq*16+g)*8), p1=*(const float2*)(smem_raw+OFF_ROW+(wg*64+wq*16+g+8)*8);
    const float nm0=p0.x, r0=p0.y, nm1=p1.x, r1=p1.y;
    wg_wait<0>();
    STAMP(2+wg*16);
    if(lane==0){ mbar_arrive_n(pwb+8*B_WEMPTY+8, (wg && SKW)? 2:1); mbar_arrive_cl(mapa(bar+8*(B_PRDY+wg), rank^1)); }
    uint32_t act[44], actp[44];
    const float sc0=0.5f*r0*r0, sc1=0.5f*r1*r1;
    const uint32_t adst = mapa(xbase+wq*8192+lane*16, rank^1), abar = mapa(bar+8*(B_AFULL+wg), rank^1);
    {
      const float4* cs = (const float4*)(smem_raw+OFF_CS);
      const float h0=0.5f*r0, h1=0.5f*r1;
      mbar_wait(bar+8*(B_PRDY+wg), 0);
      #pragma unroll
      for(int j=0;j<22;j++){
        const float4 c4=cs[4*j+t];
        const float g0=fmaf(nm0,c4.x,ag[4*j+0]), g1=fmaf(nm0,c4.y,ag[4*j+1]), g2=fmaf(nm1,c4.x,ag[4*j+2]), g3=fmaf(nm1,c4.y,ag[4*j+3]);
        const float y0=g0*fmaf(nm0,c4.z,au[4*j+0]), y1=g1*fmaf(nm0,c4.w,au[4*j+1]), y2=g2*fmaf(nm1,c4.z,au[4*j+2]), y3=g3*fmaf(nm1,c4.w,au[4*j+3]);
        act[2*j]  =pack_bf16(fmaf(y0,tanh_fast(g0*h0),y0), fmaf(y1,tanh_fast(g1*h0),y1));
        act[2*j+1]=pack_bf16(fmaf(y2,tanh_fast(g2*h1),y2), fmaf(y3,tanh_fast(g3*h1),y3));
        if((j&3)==3 && (j>>2)<NIN){ const int kk=j>>2; st_async128(adst+kk*512, act[4*kk],act[4*kk+1],act[4*kk+2],act[4*kk+3], abar); }
      }
    }
    STAMP(3+wg*16);
    if(wg==1 || !SEND0){
      #pragma unroll
      for(int kk=NIN;kk<11;kk++) st_async128(adst+kk*512, act[4*kk],act[4*kk+1],act[4*kk+2],act[4*kk+3], abar);
    }
    float acc2[2][32];
    #pragma unroll
    for(int i=0;i<32;i++){ acc2[0][i]=0.f; acc2[1][i]=0.f; }
    const uint32_t wbase = xbase+wq*8192;
    const uint32_t srow = ((~lane&4)<<1) | ((~lane&1)<<2) | (lane&2) | ((lane>>3)&1);
    const int orow = pos2row(wg*1024+rt*64+wq*16+5);
    auto flush=[&](const float* a, int c){
      #pragma unroll
      for(int kk=0;kk<4;kk++){
        uint32_t o0=pack_bf16(a[8*kk]*sc0,a[8*kk+1]*sc0), o1=pack_bf16(a[8*kk+2]*sc1,a[8*kk+3]*sc1), o2=pack_bf16(a[8*kk+4]*sc0,a[8*kk+5]*sc0), o3=pack_bf16(a[8*kk+6]*sc1,a[8*kk+7]*sc1);
        if(c==0){
          uint32_t h0,h1,h2,h3; ldsm4t(sb+(wg? OFF_RES1:OFF_RES0)+kk*2048+((lane&7)+8*(lane>>4))*128+(((2*wq+((lane>>3)&1))^(lane&7))<<4), h0,h1,h2,h3);
          o0=hadd2_bf16(o0,h0); o1=hadd2_bf16(o1,h1); o2=hadd2_bf16(o2,h2); o3=hadd2_bf16(o3,h3);
        }
        stsm4_nm(wbase+c*2048+srow*128+(((2*kk+(lane>>4))^(srow&7))<<4), o0,o1,o2,o3);
      }
      asm volatile("fence.proxy.async.shared::cta;":::"memory");
      __syncwarp();
      if(elect_one()){
        const int col = rank*256+((fp+c)&3)*64;
        tma4d_red_add(&maps.out, col, orow&7, (orow>>3)&15, orow>>7, wbase+c*2048);
        asm volatile("cp.async.bulk.commit_group;":::"memory");
      }
    };
    #pragma unroll
    for(int i=0;i<8;i++){
      const int ch = (G2_CH>>(4*i))&3, peer = (G2_PEER>>i)&1;
      constexpr int S0=(16+SKW)%NS, P0=((16+SKW)/NS)&1;
      const int slot=(S0+i)%NS, pslot=(S0+i+NS-1)%NS, ph=(P0+(S0+i)/NS)&1;
      if(i==APOS){
        mbar_wait(bar+8*(B_AFULL+wg), 0);
        #pragma unroll
        for(int kk=0;kk<11;kk++) lds128_nm(wbase+lane*16+kk*512, actp[4*kk],actp[4*kk+1],actp[4*kk+2],actp[4*kk+3]);
      }
      mbar_wait(bar+8*(B_WFULL+slot), ph);
      if(i==4 || i==6 || (i==0 && wg==1)) asm volatile("bar.sync %0, 256;"::"r"(2+wg):"memory");
      const uint64_t db = make_desc(sb+OFF_W+(5-slot)*WSLOT, 0, 1024, 1);
      wg_fence();
      #pragma unroll
      for(int kk=0;kk<11;kk++){
        if(peer) wgmma_rs<64,1>(acc2[ch&1], actp[4*kk],actp[4*kk+1],actp[4*kk+2],actp[4*kk+3], db+kk*128, 1);
        else     wgmma_rs<64,1>(acc2[ch&1], act[4*kk],act[4*kk+1],act[4*kk+2],act[4*kk+3], db+kk*128, kk>0);
      }
      wg_commit();
      if(SEND0 && i==0 && wg==0){
        #pragma unroll
        for(int kk=NIN;kk<11;kk++) st_async128(adst+kk*512, act[4*kk],act[4*kk+1],act[4*kk+2],act[4*kk+3], abar);
      }
      if(i==3 || i==5 || (i==7 && wg==0)) asm volatile("bar.arrive %0, 256;"::"r"(3-wg):"memory");
      if(i==1 || i==2){ wg_wait<1>(); if(lane==0) mbar_arrive(bar+8*(B_WEMPTY+pslot)); }
      if(i==3){ wg_wait<1>(); flush(acc2[0], 0); wg_wait<0>(); flush(acc2[1], 1); }
      if(i==5){ wg_wait<0>(); flush(acc2[0], 2); }
      STAMP(32+wg*16+i);
    }
    wg_wait<0>();
    STAMP(4+wg*16);
    flush(acc2[1], 3);
    STAMP(5+wg*16);
    asm volatile("cp.async.bulk.wait_group.read 0;":::"memory");
    STAMP(6+wg*16);
  }
  __syncwarp();
  asm volatile("barrier.cluster.arrive.relaxed.aligned;":::"memory");
  asm volatile("barrier.cluster.wait.aligned;":::"memory");
}

typedef CUresult (*PFN_encodeTiled)(CUtensorMap*, CUtensorMapDataType, cuuint32_t, void*, const cuuint64_t*, const cuuint64_t*, const cuuint32_t*, const cuuint32_t*, CUtensorMapInterleave, CUtensorMapSwizzle, CUtensorMapL2promotion, CUtensorMapFloatOOBfill);
static void make2d(PFN_encodeTiled enc, CUtensorMap* m, const void* p, uint64_t d0, uint64_t d1, uint32_t b0, uint32_t b1){
  cuuint64_t gd[2]={d0,d1}; cuuint64_t gs[1]={d0*2}; cuuint32_t bx[2]={b0,b1}; cuuint32_t es[2]={1,1};
  enc(m,CU_TENSOR_MAP_DATA_TYPE_BFLOAT16,2,(void*)p,gd,gs,bx,es,CU_TENSOR_MAP_INTERLEAVE_NONE,CU_TENSOR_MAP_SWIZZLE_128B,CU_TENSOR_MAP_L2_PROMOTION_L2_128B,CU_TENSOR_MAP_FLOAT_OOB_FILL_NONE);
}
static void make3d(PFN_encodeTiled enc, CUtensorMap* m, const void* p, uint64_t d0, uint64_t d1, uint64_t d2, uint64_t s1, uint64_t s2, uint32_t b0, uint32_t b1, uint32_t b2, CUtensorMapSwizzle sw, CUtensorMapL2promotion pr){
  cuuint64_t gd[3]={d0,d1,d2}; cuuint64_t gs[2]={s1,s2}; cuuint32_t bx[3]={b0,b1,b2}; cuuint32_t es[3]={1,1,1};
  enc(m,CU_TENSOR_MAP_DATA_TYPE_BFLOAT16,3,(void*)p,gd,gs,bx,es,CU_TENSOR_MAP_INTERLEAVE_NONE,sw,pr,CU_TENSOR_MAP_FLOAT_OOB_FILL_NONE);
}

extern "C" void kernel_launch(void* const* d_in, const int* in_sizes, int n_in, void* d_out, int out_size){
  const bf16* q=(const bf16*)d_in[0]; const bf16* k=(const bf16*)d_in[1]; const bf16* v=(const bf16*)d_in[2];
  const bf16* sh=(const bf16*)d_in[3]; const bf16* K=(const bf16*)d_in[4]; const bf16* Dv=(const bf16*)d_in[5];
  const bf16* wgt=(const bf16*)d_in[7]; const bf16* wup=(const bf16*)d_in[8]; const bf16* wdn=(const bf16*)d_in[9];
  void* fn=nullptr; cudaDriverEntryPointQueryResult qr; cudaGetDriverEntryPoint("cuTensorMapEncodeTiled",&fn,cudaEnableDefault,&qr);
  PFN_encodeTiled enc=(PFN_encodeTiled)fn;
  void* hT; cudaGetSymbolAddress(&hT,g_hT);
  Maps maps;
  make3d(enc,&maps.k,k,512,256,8,8192,1024,8,17,8,CU_TENSOR_MAP_SWIZZLE_NONE,CU_TENSOR_MAP_L2_PROMOTION_L2_128B);
  make3d(enc,&maps.v,v,512,256,8,8192,1024,8,16,8,CU_TENSOR_MAP_SWIZZLE_NONE,CU_TENSOR_MAP_L2_PROMOTION_L2_128B);
  make2d(enc,&maps.wg64,wgt,F_,D_,64,32); make2d(enc,&maps.wg48,wgt,F_,D_,48,32);
  make2d(enc,&maps.wu64,wup,F_,D_,64,32); make2d(enc,&maps.wu48,wup,F_,D_,48,32);
  make2d(enc,&maps.wd,wdn,D_,F_,64,176);
  make2d(enc,&maps.ht,hT,S_,D_,64,32);
  { cuuint64_t gd[4]={512,8,16,16}; cuuint64_t gs[3]={1024,8192,131072}; cuuint32_t bx[4]={64,2,4,2}; cuuint32_t es[4]={1,1,1,1};
    enc(&maps.out,CU_TENSOR_MAP_DATA_TYPE_BFLOAT16,4,d_out,gd,gs,bx,es,CU_TENSOR_MAP_INTERLEAVE_NONE,CU_TENSOR_MAP_SWIZZLE_128B,CU_TENSOR_MAP_L2_PROMOTION_NONE,CU_TENSOR_MAP_FLOAT_OOB_FILL_NONE); }
  void* xa; cudaGetSymbolAddress(&xa,g_xa);
  make2d(enc,&maps.xa,xa,8192,128,64,128);
  cudaFuncSetAttribute(fused_kernel,cudaFuncAttributeMaxDynamicSharedMemorySize,SMEM_BYTES);
  fused_kernel<<<128,384,SMEM_BYTES>>>(maps,q,sh,K,Dv,wgt,wup,wdn,(bf16*)d_out);
}
```

```cpp
#include <cuda_runtime.h>
#include <cuda_bf16.h>
#include <cuda.h>
#include <stdint.h>

template<int TA,int TB> __device__ __forceinline__ void wgmma_ss_n176(float* d, uint64_t da, uint64_t db, int sd){
  asm volatile("{ .reg .pred p; setp.ne.b32 p, %90, 0; wgmma.mma_async.sync.aligned.m64n176k16.f32.bf16.bf16 {%0,%1,%2,%3,%4,%5,%6,%7,%8,%9,%10,%11,%12,%13,%14,%15,%16,%17,%18,%19,%20,%21,%22,%23,%24,%25,%26,%27,%28,%29,%30,%31,%32,%33,%34,%35,%36,%37,%38,%39,%40,%41,%42,%43,%44,%45,%46,%47,%48,%49,%50,%51,%52,%53,%54,%55,%56,%57,%58,%59,%60,%61,%62,%63,%64,%65,%66,%67,%68,%69,%70,%71,%72,%73,%74,%75,%76,%77,%78,%79,%80,%81,%82,%83,%84,%85,%86,%87}, %88, %89, p, 1, 1, %91, %92; }"
   : "+f"(d[0]),"+f"(d[1]),"+f"(d[2]),"+f"(d[3]),"+f"(d[4]),"+f"(d[5]),"+f"(d[6]),"+f"(d[7]),"+f"(d[8]),"+f"(d[9]),"+f"(d[10]),"+f"(d[11]),"+f"(d[12]),"+f"(d[13]),"+f"(d[14]),"+f"(d[15]),"+f"(d[16]),"+f"(d[17]),"+f"(d[18]),"+f"(d[19]),"+f"(d[20]),"+f"(d[21]),"+f"(d[22]),"+f"(d[23]),"+f"(d[24]),"+f"(d[25]),"+f"(d[26]),"+f"(d[27]),"+f"(d[28]),"+f"(d[29]),"+f"(d[30]),"+f"(d[31]),"+f"(d[32]),"+f"(d[33]),"+f"(d[34]),"+f"(d[35]),"+f"(d[36]),"+f"(d[37]),"+f"(d[38]),"+f"(d[39]),"+f"(d[40]),"+f"(d[41]),"+f"(d[42]),"+f"(d[43]),"+f"(d[44]),"+f"(d[45]),"+f"(d[46]),"+f"(d[47]),"+f"(d[48]),"+f"(d[49]),"+f"(d[50]),"+f"(d[51]),"+f"(d[52]),"+f"(d[53]),"+f"(d[54]),"+f"(d[55]),"+f"(d[56]),"+f"(d[57]),"+f"(d[58]),"+f"(d[59]),"+f"(d[60]),"+f"(d[61]),"+f"(d[62]),"+f"(d[63]),"+f"(d[64]),"+f"(d[65]),"+f"(d[66]),"+f"(d[67]),"+f"(d[68]),"+f"(d[69]),"+f"(d[70]),"+f"(d[71]),"+f"(d[72]),"+f"(d[73]),"+f"(d[74]),"+f"(d[75]),"+f"(d[76]),"+f"(d[77]),"+f"(d[78]),"+f"(d[79]),"+f"(d[80]),"+f"(d[81]),"+f"(d[82]),"+f"(d[83]),"+f"(d[84]),"+f"(d[85]),"+f"(d[86]),"+f"(d[87]) : "l"(da), "l"(db), "r"(sd), "n"(TA), "n"(TB));
}
template<int TB> __device__ __forceinline__ void wgmma_rs_n8(float* d, uint32_t a0, uint32_t a1, uint32_t a2, uint32_t a3, uint64_t db, int sd){
  asm volatile("{ .reg .pred p; setp.ne.b32 p, %9, 0; wgmma.mma_async.sync.aligned.m64n8k16.f32.bf16.bf16 {%0,%1,%2,%3}, {%4,%5,%6,%7}, %8, p, 1, 1, %10; }"
   : "+f"(d[0]),"+f"(d[1]),"+f"(d[2]),"+f"(d[3]) : "r"(a0),"r"(a1),"r"(a2),"r"(a3), "l"(db), "r"(sd), "n"(TB));
}
template<int TB> __device__ __forceinline__ void wgmma_rs_n16(float* d, uint32_t a0, uint32_t a1, uint32_t a2, uint32_t a3, uint64_t db, int sd){
  asm volatile("{ .reg .pred p; setp.ne.b32 p, %13, 0; wgmma.mma_async.sync.aligned.m64n16k16.f32.bf16.bf16 {%0,%1,%2,%3,%4,%5,%6,%7}, {%8,%9,%10,%11}, %12, p, 1, 1, %14; }"
   : "+f"(d[0]),"+f"(d[1]),"+f"(d[2]),"+f"(d[3]),"+f"(d[4]),"+f"(d[5]),"+f"(d[6]),"+f"(d[7]) : "r"(a0),"r"(a1),"r"(a2),"r"(a3), "l"(db), "r"(sd), "n"(TB));
}
template<int TB> __device__ __forceinline__ void wgmma_rs_n24(float* d, uint32_t a0, uint32_t a1, uint32_t a2, uint32_t a3, uint64_t db, int sd){
  asm volatile("{ .reg .pred p; setp.ne.b32 p, %17, 0; wgmma.mma_async.sync.aligned.m64n24k16.f32.bf16.bf16 {%0,%1,%2,%3,%4,%5,%6,%7,%8,%9,%10,%11}, {%12,%13,%14,%15}, %16, p, 1, 1, %18; }"
   : "+f"(d[0]),"+f"(d[1]),"+f"(d[2]),"+f"(d[3]),"+f"(d[4]),"+f"(d[5]),"+f"(d[6]),"+f"(d[7]),"+f"(d[8]),"+f"(d[9]),"+f"(d[10]),"+f"(d[11]) : "r"(a0),"r"(a1),"r"(a2),"r"(a3), "l"(db), "r"(sd), "n"(TB));
}
template<int TB> __device__ __forceinline__ void wgmma_rs_n32(float* d, uint32_t a0, uint32_t a1, uint32_t a2, uint32_t a3, uint64_t db, int sd){
  asm volatile("{ .reg .pred p; setp.ne.b32 p, %21, 0; wgmma.mma_async.sync.aligned.m64n32k16.f32.bf16.bf16 {%0,%1,%2,%3,%4,%5,%6,%7,%8,%9,%10,%11,%12,%13,%14,%15}, {%16,%17,%18,%19}, %20, p, 1, 1, %22; }"
   : "+f"(d[0]),"+f"(d[1]),"+f"(d[2]),"+f"(d[3]),"+f"(d[4]),"+f"(d[5]),"+f"(d[6]),"+f"(d[7]),"+f"(d[8]),"+f"(d[9]),"+f"(d[10]),"+f"(d[11]),"+f"(d[12]),"+f"(d[13]),"+f"(d[14]),"+f"(d[15]) : "r"(a0),"r"(a1),"r"(a2),"r"(a3), "l"(db), "r"(sd), "n"(TB));
}
template<int TB> __device__ __forceinline__ void wgmma_rs_n40(float* d, uint32_t a0, uint32_t a1, uint32_t a2, uint32_t a3, uint64_t db, int sd){
  asm volatile("{ .reg .pred p; setp.ne.b32 p, %25, 0; wgmma.mma_async.sync.aligned.m64n40k16.f32.bf16.bf16 {%0,%1,%2,%3,%4,%5,%6,%7,%8,%9,%10,%11,%12,%13,%14,%15,%16,%17,%18,%19}, {%20,%21,%22,%23}, %24, p, 1, 1, %26; }"
   : "+f"(d[0]),"+f"(d[1]),"+f"(d[2]),"+f"(d[3]),"+f"(d[4]),"+f"(d[5]),"+f"(d[6]),"+f"(d[7]),"+f"(d[8]),"+f"(d[9]),"+f"(d[10]),"+f"(d[11]),"+f"(d[12]),"+f"(d[13]),"+f"(d[14]),"+f"(d[15]),"+f"(d[16]),"+f"(d[17]),"+f"(d[18]),"+f"(d[19]) : "r"(a0),"r"(a1),"r"(a2),"r"(a3), "l"(db), "r"(sd), "n"(TB));
}
template<int TB> __device__ __forceinline__ void wgmma_rs_n48(float* d, uint32_t a0, uint32_t a1, uint32_t a2, uint32_t a3, uint64_t db, int sd){
  asm volatile("{ .reg .pred p; setp.ne.b32 p, %29, 0; wgmma.mma_async.sync.aligned.m64n48k16.f32.bf16.bf16 {%0,%1,%2,%3,%4,%5,%6,%7,%8,%9,%10,%11,%12,%13,%14,%15,%16,%17,%18,%19,%20,%21,%22,%23}, {%24,%25,%26,%27}, %28, p, 1, 1, %30; }"
   : "+f"(d[0]),"+f"(d[1]),"+f"(d[2]),"+f"(d[3]),"+f"(d[4]),"+f"(d[5]),"+f"(d[6]),"+f"(d[7]),"+f"(d[8]),"+f"(d[9]),"+f"(d[10]),"+f"(d[11]),"+f"(d[12]),"+f"(d[13]),"+f"(d[14]),"+f"(d[15]),"+f"(d[16]),"+f"(d[17]),"+f"(d[18]),"+f"(d[19]),"+f"(d[20]),"+f"(d[21]),"+f"(d[22]),"+f"(d[23]) : "r"(a0),"r"(a1),"r"(a2),"r"(a3), "l"(db), "r"(sd), "n"(TB));
}
template<int TB> __device__ __forceinline__ void wgmma_rs_n56(float* d, uint32_t a0, uint32_t a1, uint32_t a2, uint32_t a3, uint64_t db, int sd){
  asm volatile("{ .reg .pred p; setp.ne.b32 p, %33, 0; wgmma.mma_async.sync.aligned.m64n56k16.f32.bf16.bf16 {%0,%1,%2,%3,%4,%5,%6,%7,%8,%9,%10,%11,%12,%13,%14,%15,%16,%17,%18,%19,%20,%21,%22,%23,%24,%25,%26,%27}, {%28,%29,%30,%31}, %32, p, 1, 1, %34; }"
   : "+f"(d[0]),"+f"(d[1]),"+f"(d[2]),"+f"(d[3]),"+f"(d[4]),"+f"(d[5]),"+f"(d[6]),"+f"(d[7]),"+f"(d[8]),"+f"(d[9]),"+f"(d[10]),"+f"(d[11]),"+f"(d[12]),"+f"(d[13]),"+f"(d[14]),"+f"(d[15]),"+f"(d[16]),"+f"(d[17]),"+f"(d[18]),"+f"(d[19]),"+f"(d[20]),"+f"(d[21]),"+f"(d[22]),"+f"(d[23]),"+f"(d[24]),"+f"(d[25]),"+f"(d[26]),"+f"(d[27]) : "r"(a0),"r"(a1),"r"(a2),"r"(a3), "l"(db), "r"(sd), "n"(TB));
}
template<int TB> __device__ __forceinline__ void wgmma_rs_n64(float* d, uint32_t a0, uint32_t a1, uint32_t a2, uint32_t a3, uint64_t db, int sd){
  asm volatile("{ .reg .pred p; setp.ne.b32 p, %37, 0; wgmma.mma_async.sync.aligned.m64n64k16.f32.bf16.bf16 {%0,%1,%2,%3,%4,%5,%6,%7,%8,%9,%10,%11,%12,%13,%14,%15,%16,%17,%18,%19,%20,%21,%22,%23,%24,%25,%26,%27,%28,%29,%30,%31}, {%32,%33,%34,%35}, %36, p, 1, 1, %38; }"
   : "+f"(d[0]),"+f"(d[1]),"+f"(d[2]),"+f"(d[3]),"+f"(d[4]),"+f"(d[5]),"+f"(d[6]),"+f"(d[7]),"+f"(d[8]),"+f"(d[9]),"+f"(d[10]),"+f"(d[11]),"+f"(d[12]),"+f"(d[13]),"+f"(d[14]),"+f"(d[15]),"+f"(d[16]),"+f"(d[17]),"+f"(d[18]),"+f"(d[19]),"+f"(d[20]),"+f"(d[21]),"+f"(d[22]),"+f"(d[23]),"+f"(d[24]),"+f"(d[25]),"+f"(d[26]),"+f"(d[27]),"+f"(d[28]),"+f"(d[29]),"+f"(d[30]),"+f"(d[31]) : "r"(a0),"r"(a1),"r"(a2),"r"(a3), "l"(db), "r"(sd), "n"(TB));
}
template<int N,int TA,int TB> __device__ __forceinline__ void wgmma_ss(float* d, uint64_t da, uint64_t db, int sd){
  if constexpr(N==176) wgmma_ss_n176<TA,TB>(d,da,db,sd);
}
template<int N,int TB> __device__ __forceinline__ void wgmma_rs(float* d, uint32_t a0,uint32_t a1,uint32_t a2,uint32_t a3, uint64_t db, int sd){
  if constexpr(N==8) wgmma_rs_n8<TB>(d,a0,a1,a2,a3,db,sd);
  if constexpr(N==16) wgmma_rs_n16<TB>(d,a0,a1,a2,a3,db,sd);
  if constexpr(N==24) wgmma_rs_n24<TB>(d,a0,a1,a2,a3,db,sd);
  if constexpr(N==32) wgmma_rs_n32<TB>(d,a0,a1,a2,a3,db,sd);
  if constexpr(N==40) wgmma_rs_n40<TB>(d,a0,a1,a2,a3,db,sd);
  if constexpr(N==48) wgmma_rs_n48<TB>(d,a0,a1,a2,a3,db,sd);
  if constexpr(N==56) wgmma_rs_n56<TB>(d,a0,a1,a2,a3,db,sd);
  if constexpr(N==64) wgmma_rs_n64<TB>(d,a0,a1,a2,a3,db,sd);
}

typedef __nv_bfloat16 bf16;
constexpr int S_ = 2048, D_ = 512, F_ = 1376, FS = 176;

__device__ __forceinline__ uint32_t smem_u32(const void* p){ return (uint32_t)__cvta_generic_to_shared(p); }
__device__ __forceinline__ void mbar_init(uint32_t bar, uint32_t cnt){ asm volatile("mbarrier.init.shared::cta.b64 [%0], %1;"::"r"(bar),"r"(cnt):"memory"); }
__device__ __forceinline__ void mbar_expect_tx(uint32_t bar, uint32_t bytes){ asm volatile("mbarrier.arrive.expect_tx.shared::cta.b64 _, [%0], %1;"::"r"(bar),"r"(bytes):"memory"); }
__device__ __forceinline__ void mbar_arrive(uint32_t bar){ asm volatile("mbarrier.arrive.shared::cta.b64 _, [%0];"::"r"(bar):"memory"); }
__device__ __forceinline__ void mbar_arrive_n(uint32_t bar, uint32_t n){ asm volatile("mbarrier.arrive.shared::cta.b64 _, [%0], %1;"::"r"(bar),"r"(n):"memory"); }
__device__ __forceinline__ void mbar_arrive_cl(uint32_t cbar){ asm volatile("mbarrier.arrive.shared::cluster.b64 _, [%0];"::"r"(cbar):"memory"); }
__device__ __forceinline__ uint32_t mapa(uint32_t a, uint32_t cta){ uint32_t r; asm volatile("mapa.shared::cluster.u32 %0, %1, %2;":"=r"(r):"r"(a),"r"(cta)); return r; }
__device__ __forceinline__ void mbar_wait(uint32_t bar, uint32_t ph){
  asm volatile("{ .reg .pred p; .reg .u32 c; mov.u32 c, 0;\n"
               "WL: mbarrier.try_wait.parity.shared::cta.b64 p, [%0], %1; @p bra WD; add.u32 c,c,1; setp.lt.u32 p, c, 2000000; @p bra WL; trap;\n"
               "WD: }"::"r"(bar),"r"(ph):"memory"); }
__device__ __forceinline__ uint32_t mbar_test(uint32_t bar, uint32_t ph){ uint32_t ok; asm volatile("{ .reg .pred p; mbarrier.test_wait.parity.shared::cta.b64 p, [%1], %2; selp.u32 %0,1,0,p; }":"=r"(ok):"r"(bar),"r"(ph):"memory"); return ok; }
__device__ __forceinline__ void spin_guard(int n){ asm volatile("{ .reg .pred p; setp.gt.s32 p, %0, 2000000; @p trap; }"::"r"(n)); }
__device__ __forceinline__ bool elect_one(){ uint32_t p; asm volatile("{ .reg .pred P; elect.sync _|P, 0xffffffff; selp.u32 %0,1,0,P; }":"=r"(p)); return p; }
__device__ __forceinline__ void tma2d(uint32_t dst, const CUtensorMap* m, int c0, int c1, uint32_t bar){
  asm volatile("cp.async.bulk.tensor.2d.shared::cluster.global.mbarrier::complete_tx::bytes [%0], [%1, {%3, %4}], [%2];"::"r"(dst),"l"(m),"r"(bar),"r"(c0),"r"(c1):"memory"); }
__device__ __forceinline__ void tma2d_mc(uint32_t dst, const CUtensorMap* m, int c0, int c1, uint32_t bar){
  asm volatile("cp.async.bulk.tensor.2d.shared::cluster.global.mbarrier::complete_tx::bytes.multicast::cluster [%0], [%1, {%3, %4}], [%2], %5;"::"r"(dst),"l"(m),"r"(bar),"r"(c0),"r"(c1),"h"((uint16_t)3):"memory"); }
__device__ __forceinline__ void cluster_sync(){ asm volatile("barrier.cluster.arrive.release.aligned; barrier.cluster.wait.acquire.aligned;":::"memory"); }
__device__ __forceinline__ void wg_fence(){ asm volatile("wgmma.fence.sync.aligned;":::"memory"); }
__device__ __forceinline__ void wg_commit(){ asm volatile("wgmma.commit_group.sync.aligned;":::"memory"); }
template<int N> __device__ __forceinline__ void wg_wait(){ asm volatile("wgmma.wait_group.sync.aligned %0;"::"n"(N):"memory"); }
__device__ __forceinline__ uint64_t make_desc(uint32_t addr, uint32_t lbo, uint32_t sbo, uint32_t sw){ return (uint64_t)((addr&0x3FFFF)>>4) | ((uint64_t)((lbo&0x3FFFF)>>4)<<16) | ((uint64_t)((sbo&0x3FFFF)>>4)<<32) | ((uint64_t)sw<<62); }
__device__ __forceinline__ void ldsm4t(uint32_t a, uint32_t& r0, uint32_t& r1, uint32_t& r2, uint32_t& r3){ asm volatile("ldmatrix.sync.aligned.m8n8.x4.trans.shared.b16 {%0,%1,%2,%3}, [%4];":"=r"(r0),"=r"(r1),"=r"(r2),"=r"(r3):"r"(a):"memory"); }
__device__ __forceinline__ void stsm4(uint32_t a, uint32_t r0, uint32_t r1, uint32_t r2, uint32_t r3){ asm volatile("stmatrix.sync.aligned.m8n8.x4.shared.b16 [%0], {%1,%2,%3,%4};"::"r"(a),"r"(r0),"r"(r1),"r"(r2),"r"(r3):"memory"); }
__device__ __forceinline__ uint32_t pack_bf16(float lo, float hi){ uint32_t r; asm("cvt.rn.bf16x2.f32 %0, %1, %2;":"=r"(r):"f"(hi),"f"(lo)); return r; }
__device__ __forceinline__ float bf_lo(uint32_t v){ return __uint_as_float(v<<16); }
__device__ __forceinline__ float bf_hi(uint32_t v){ return __uint_as_float(v&0xffff0000u); }
__device__ __forceinline__ float rbf(float x){ return __bfloat162float(__float2bfloat16(x)); }
__device__ __forceinline__ uint32_t hadd2_bf16(uint32_t a, uint32_t b){ uint32_t r; asm("add.rn.bf16x2 %0, %1, %2;":"=r"(r):"r"(a),"r"(b)); return r; }
__device__ __forceinline__ float tanh_fast(float x){ float r; asm("tanh.approx.f32 %0, %1;":"=f"(r):"f"(x)); return r; }

__device__ __forceinline__ void st_rlx128(void* p, uint32_t a, uint32_t b, uint32_t c, uint32_t d){
  asm volatile("{ .reg .b64 l,h; .reg .b128 v; mov.b64 l,{%1,%2}; mov.b64 h,{%3,%4}; mov.b128 v,{l,h}; st.relaxed.gpu.global.b128 [%0], v; }"::"l"(p),"r"(a),"r"(b),"r"(c),"r"(d):"memory"); }
__device__ __forceinline__ void ld_rlx128(const void* p, uint4& v){
  asm volatile("{ .reg .b64 l,h; .reg .b128 v; ld.relaxed.gpu.global.b128 v, [%4]; mov.b128 {l,h}, v; mov.b64 {%0,%1}, l; mov.b64 {%2,%3}, h; }":"=r"(v.x),"=r"(v.y),"=r"(v.z),"=r"(v.w):"l"(p):"memory"); }
__device__ __forceinline__ void st_async128(uint32_t dst, uint32_t a, uint32_t b, uint32_t c, uint32_t d, uint32_t cbar){
  asm volatile("st.async.weak.shared::cluster.mbarrier::complete_tx::bytes.v4.b32 [%0], {%1,%2,%3,%4}, [%5];"::"r"(dst),"r"(a),"r"(b),"r"(c),"r"(d),"r"(cbar)); }
__device__ __forceinline__ void st_async32(uint32_t dst, uint32_t a, uint32_t cbar){
  asm volatile("st.async.weak.shared::cluster.mbarrier::complete_tx::bytes.b32 [%0], %1, [%2];"::"r"(dst),"r"(a),"r"(cbar)); }
__device__ __forceinline__ void mbar_wait_nomem(uint32_t bar, uint32_t ph){
  asm volatile("{ .reg .pred p; .reg .u32 c; mov.u32 c, 0;\n"
               "WL: mbarrier.try_wait.parity.shared::cta.b64 p, [%0], %1; @p bra WD; add.u32 c,c,1; setp.lt.u32 p, c, 2000000; @p bra WL; trap;\n"
               "WD: }"::"r"(bar),"r"(ph)); }
__device__ __forceinline__ void bulk_g2s(uint32_t dst, const void* src, uint32_t bytes, uint32_t bar){
  asm volatile("cp.async.bulk.shared::cluster.global.mbarrier::complete_tx::bytes [%0], [%1], %2, [%3];"::"r"(dst),"l"(src),"r"(bytes),"r"(bar):"memory"); }
__device__ __forceinline__ void mbar_wait_cl(uint32_t bar, uint32_t ph){
  asm volatile("{ .reg .pred p; .reg .u32 c; mov.u32 c, 0;\n"
               "WL: mbarrier.try_wait.parity.acquire.cluster.shared::cta.b64 p, [%0], %1; @p bra WD; add.u32 c,c,1; setp.lt.u32 p, c, 2000000; @p bra WL; trap;\n"
               "WD: }"::"r"(bar),"r"(ph):"memory"); }
__device__ __forceinline__ void lds128(uint32_t a, uint32_t& x, uint32_t& y, uint32_t& z, uint32_t& w){ asm volatile("ld.shared.v4.u32 {%0,%1,%2,%3}, [%4];":"=r"(x),"=r"(y),"=r"(z),"=r"(w):"r"(a):"memory"); }
__device__ __forceinline__ void tma4d_red_add(const CUtensorMap* m, int c0, int c1, int c2, int c3, uint32_t src){
  asm volatile("cp.reduce.async.bulk.tensor.4d.global.shared::cta.add.tile.bulk_group [%0, {%1, %2, %3, %4}], [%5];"::"l"(m),"r"(c0),"r"(c1),"r"(c2),"r"(c3),"r"(src):"memory"); }
__device__ __forceinline__ void stsm4_nm(uint32_t a, uint32_t r0, uint32_t r1, uint32_t r2, uint32_t r3){ asm volatile("stmatrix.sync.aligned.m8n8.x4.shared.b16 [%0], {%1,%2,%3,%4};"::"r"(a),"r"(r0),"r"(r1),"r"(r2),"r"(r3)); }
__device__ __forceinline__ void tma3d(uint32_t dst, const CUtensorMap* m, int c0, int c1, int c2, uint32_t bar){
  asm volatile("cp.async.bulk.tensor.3d.shared::cluster.global.mbarrier::complete_tx::bytes [%0], [%1, {%3, %4, %5}], [%2];"::"r"(dst),"l"(m),"r"(bar),"r"(c0),"r"(c1),"r"(c2):"memory"); }
__device__ __forceinline__ uint32_t lds32(uint32_t a){ uint32_t v; asm volatile("ld.shared.u32 %0, [%1];":"=r"(v):"r"(a)); return v; }
__device__ __forceinline__ void sts128(uint32_t a, uint32_t x, uint32_t y, uint32_t z, uint32_t w){ asm volatile("st.shared.v4.u32 [%0], {%1,%2,%3,%4};"::"r"(a),"r"(x),"r"(y),"r"(z),"r"(w):"memory"); }
__device__ __forceinline__ uint4 ldg_nc128(const void* p){ uint4 v; asm volatile("ld.global.nc.L1::no_allocate.v4.u32 {%0,%1,%2,%3}, [%4];":"=r"(v.x),"=r"(v.y),"=r"(v.z),"=r"(v.w):"l"(p)); return v; }
__device__ __forceinline__ uint32_t hmul2_bf16(uint32_t a, uint32_t b){ uint32_t r; asm("mul.rn.bf16x2 %0, %1, %2;":"=r"(r):"r"(a),"r"(b)); return r; }
__device__ __forceinline__ uint32_t hfma2_bf16(uint32_t a, uint32_t b, uint32_t c){ uint32_t r; asm("fma.rn.bf16x2 %0, %1, %2, %3;":"=r"(r):"r"(a),"r"(b),"r"(c)); return r; }
__device__ __forceinline__ uint32_t hsub2_bf16(uint32_t a, uint32_t b){ uint32_t r; asm("sub.rn.bf16x2 %0, %1, %2;":"=r"(r):"r"(a),"r"(b)); return r; }
__device__ __forceinline__ void poll_ge(const unsigned* p, unsigned target){
  unsigned v; int n=0;
  do{ asm volatile("ld.acquire.gpu.global.u32 %0, [%1];":"=r"(v):"l"(p):"memory"); spin_guard(++n); }while((int)(v-target)<0); }
__device__ __forceinline__ void signal_add(unsigned* p){ asm volatile("fence.acq_rel.gpu;":::"memory"); asm volatile("red.relaxed.gpu.global.add.u32 [%0], 1;"::"l"(p):"memory"); }
__device__ __forceinline__ void lds128_nm(uint32_t a, uint32_t& x, uint32_t& y, uint32_t& z, uint32_t& w){ asm volatile("ld.shared.v4.u32 {%0,%1,%2,%3}, [%4];":"=r"(x),"=r"(y),"=r"(z),"=r"(w):"r"(a)); }
__device__ __forceinline__ float ln_rstd(float var){
  float sq, r; asm("sqrt.approx.f32 %0, %1;":"=f"(sq):"f"(rbf(rbf(var)+1e-5f))); asm("rcp.approx.f32 %0, %1;":"=f"(r):"f"(rbf(sq))); return r; }
__device__ __forceinline__ float4 gather_sum(const uint4* src, int n, int stride, uint32_t par){
  float4 c=make_float4(0.f,0.f,0.f,0.f);
  #pragma unroll 1
  for(int kb=0;kb<n;kb+=4){
    uint4 v[4]; int it=0;
    do{
      #pragma unroll
      for(int u=0;u<4;u++) ld_rlx128(src+u*stride, v[u]);
      spin_guard(++it);
    }while(((v[0].x^par)|(v[1].x^par)|(v[2].x^par)|(v[3].x^par))&1);
    #pragma unroll
    for(int u=0;u<4;u++){ c.x+=__uint_as_float(v[u].x); c.y+=__uint_as_float(v[u].y); c.z+=__uint_as_float(v[u].z); c.w+=__uint_as_float(v[u].w); }
    src+=4*stride;
  }
  return c;
}
__host__ __device__ __forceinline__ int pos2row(int pos){
  const int P = 1 - (pos >> 10), thr = (pos & 1023) >> 3, k = (pos>>2)&1, h = (pos>>1)&1, e = pos&1;
  const int w = thr >> 5, tp = (thr >> 3)&3, j = (thr >> 1)&3, p = thr & 1;
  return 16*(127 - (64*P + 16*j + 8*k + 2*tp + e)) + 8*h + 2*w + p;
}

__device__ __align__(1024) bf16 g_hT[D_*S_];
__device__ __align__(1024) uint4 g_xa[128*128*8];
__device__ __align__(1024) uint4 g_qs[128*8];
__device__ uint4 g_stat[16*2*8*32];
__device__ uint4 g_csp[8*16*88];
__device__ uint4 g_cs2[8*96];
__device__ __align__(512) unsigned g_hflag[2*32*32];
__device__ unsigned g_cnt[4*32];
#define STAMP(i)

#define RC 224
#define RP 56
#define STR2(x) #x
#define STR(x) STR2(x)
#define KVAHEAD 4
#define PACE 2
#define CGMAP(c) (c)
#define QDELAY 1700
#define WSTART 5
#define CSLEEP 600
#define KEPI 6
#define KV0 3
#define XPOS 3
#define PFE 0
#define CP 0
#define BARV 0
#define BSLEEP 20
#define WDPF 6
#define SKW 4
#define APOS 1
#define SEND0 0
#define KDELAY 0
#define XAFTER 4
#define XEARLY 1
#define W9 2
#define ODE 2400
#define ODL 1500
#define VN 6
#define ZPOS 0
#define STX 1
#define LD2 1
#define AP1 1
#define NIN 7
#define LEAD 0
constexpr uint32_t G2_CH = 0x33221010u, G2_PEER = 0xAC;
constexpr int NS = 6, WSLOT = 24576, NX = 4, XSLOT = 8192;
constexpr int OFF_RES0 = 0, OFF_X = 8192, OFF_RES1 = 73728, OFF_W = 81920;
constexpr int OFF_CS = OFF_W + NS*WSLOT, OFF_ROW = OFF_CS + 2*FS*4, OFF_BAR = OFF_ROW + 1024;
constexpr int TBL = 8320, UPL = 2112, UCH = 2*UPL, QP = 1088, KVCH = 4224;
constexpr int OFF_TBL = 32768, OFF_U = OFF_TBL + 4*TBL, OFF_XAL = 83968, OFF_XAE = OFF_W + 1*WSLOT;
constexpr int OFF_IMG = 0, OFF_X8 = OFF_XAL + 16384;
#define KVOFF(T) (OFF_W + 3*WSLOT + (T)*KVCH - ((T)>>2)*(WSLOT+4*KVCH))
constexpr int OFF_KV = OFF_W + 3*WSLOT, OFF_Q = OFF_W + 4*WSLOT, OFF_SK = OFF_Q + 16*QP;
static_assert(OFF_U + 4*UCH <= OFF_XAL && OFF_XAL + 16384 <= OFF_W + WSLOT, "overlay");
constexpr int B_WFULL = 0, B_WEMPTY = B_WFULL+NS, B_XFULL = B_WEMPTY+NS, B_XEMPTY = B_XFULL+2*NX, B_PRDY = B_XEMPTY+2*NX, B_AFULL = B_PRDY+2,
              B_ONE = B_AFULL+2, B_FB = B_ONE, B_INIT = B_FB+2, B_XA = B_INIT+2, B_PAR = B_XA+2, B_TD = B_PAR+2, B_KV = B_TD+1, B_U = B_KV+8, B_HD = B_U+8, B_SK = B_HD+2, B_Q = B_SK+1, B_QD = B_Q+8, B_SC = B_QD+1, B_X03 = B_SC+1, B_PK = B_X03+1, B_PH = B_PK+1, B_RT = B_PH+2, NBAR = B_RT+2;
constexpr int OFF_MISC = (OFF_BAR + NBAR*8 + 15)&~15;
constexpr int SMEM_BYTES = OFF_MISC + 16;
static_assert(SMEM_BYTES<=232448,"smem");

struct Maps { CUtensorMap k, v, xa, w64, w48, wd, ht, out; int upfirst; };

__device__ __forceinline__ void load_w_stage(const Maps& maps, uint32_t dst, int col, int k0, uint32_t fb){
  asm volatile("cp.async.bulk.tensor.4d.shared::cluster.global.mbarrier::complete_tx::bytes [%0], [%1, {%3, %4, %5, %5}], [%2];"::"r"(dst),"l"(&maps.w64),"r"(fb),"r"(col),"r"(k0),"r"(0):"memory");
  tma3d(dst+16384, &maps.w48, col+128, k0, 0, fb);
}

template<int N> __device__ __forceinline__ void conv_mma(float* acc, const uint32_t* R, uint64_t db){
  wgmma_rs<N,0>(acc, R[0],R[1],R[2],R[3], db,   1);
  wgmma_rs<N,0>(acc, R[4],R[5],R[6],R[7], db+1, 1);
}
__device__ __forceinline__ void conv_lda(uint32_t* R, const uint32_t* tb, int off){
  R[0]=lds32(tb[0]+off); R[1]=lds32(tb[1]+off); R[3]=lds32(tb[2]+off); R[5]=lds32(tb[3]+off); R[7]=lds32(tb[4]+off);
}
__device__ __forceinline__ void conv_dup(uint32_t* R){
  asm volatile("mov.b32 %0, %1;":"=r"(R[2]):"r"(R[1])); asm volatile("mov.b32 %0, %1;":"=r"(R[4]):"r"(R[3])); asm volatile("mov.b32 %0, %1;":"=r"(R[6]):"r"(R[5]));
}
__device__ __forceinline__ void zero4(float* a){
  #pragma unroll
  for(int i=0;i<4;i++) asm volatile("mov.b32 %0, 0;":"=f"(a[i]));
}
__device__ __forceinline__ uint32_t tid_now(){ uint32_t t; asm volatile("mov.u32 %0, %%tid.x;":"=r"(t)); return t; }
template<int PART> __device__ __forceinline__ void load_xa(uint4* x, uint4* a, uint32_t sb, int warp, int lane){
  const int cb = CGMAP(blockIdx.x>>1)*2+(blockIdx.x&1);
  const uint32_t tw = (warp&3)*32+lane, pq = (PART*4)^(tw&7), pc = ((warp>>2)*2)^pq;
  uint4 st[4];
  #pragma unroll
  for(int i=0;i<2;i++) lds128(sb+OFF_XAL+tw*128+((pc^i)<<4), x[i].x,x[i].y,x[i].z,x[i].w);
  #pragma unroll
  for(int i=0;i<4;i++) lds128(sb+OFF_XAE+tw*128+((i^pq)<<4), st[i].x,st[i].y,st[i].z,st[i].w);
  const uint32_t ep = lds32(sb+OFF_MISC);
  for(int n=0;n<2000000;n++){
    if(!((st[0].w^ep)|(st[1].w^ep)|(st[2].w^ep)|(st[3].w^ep)) && x[0].x && x[1].x) break;
    const uint32_t t2=tid_now()&127;
    #pragma unroll
    for(int i=0;i<2;i++) ld_rlx128(&g_xa[cb*1024+t2*8+(pc^i)], x[i]);
    #pragma unroll
    for(int i=0;i<4;i++) ld_rlx128(&g_qs[t2*8+(i^pq)], st[i]);
  }
  __syncwarp();
#define LNA(X,S) ({ const uint32_t d_=hsub2_bf16(X,S.x); hfma2_bf16(d_,S.y,hmul2_bf16(d_,S.z)); })
  #pragma unroll
  for(int i=0;i<2;i++){
    x[i].x=~x[i].x;
    a[i].x=LNA(x[i].x,st[0]); a[i].y=LNA(x[i].y,st[1]); a[i].z=LNA(x[i].z,st[2]); a[i].w=LNA(x[i].w,st[3]);
  }
}
template<int PART> __device__ __forceinline__ void conv_put(const float* a0, const float* a1, uint32_t sb, int warp, int lane){
  const uint32_t eb = sb + (PART? OFF_IMG+warp*4096 : OFF_TBL+(warp>>2)*2*TBL+(warp&3)*4096), x8 = sb+OFF_X8+warp*512;
  const uint32_t rho = (lane&24)|((lane&3)<<1)|((lane>>2)&1);
  #pragma unroll
  for(int ii=0;ii<8;ii++){
    const uint32_t w0=pack_bf16(a0[4*ii],a0[4*ii+1]), w1=pack_bf16(a0[4*ii+2],a0[4*ii+3]), w2=pack_bf16(a1[4*ii],a1[4*ii+1]), w3=pack_bf16(a1[4*ii+2],a1[4*ii+3]);
    sts128(eb+rho*128+(((rho+ii)&7)<<4), w0,w1,w2,w3);
    if(PART && ii==0) sts128(x8+rho*16, w0,w1,w2,w3);
  }
  __syncwarp();
}
template<int PART> __device__ __forceinline__ void conv_get(const uint4* x, const uint4* a, uint32_t sb, int warp, int lane){
  const int cb = CGMAP(blockIdx.x>>1)*2+(blockIdx.x&1), chl = (warp>>2)*2;
  const uint32_t tw = (warp&3)*32+lane;
  const uint32_t eb = sb + (PART? OFF_IMG+warp*4096 : OFF_TBL+(warp>>2)*2*TBL+(warp&3)*4096), x8 = sb+OFF_X8+warp*512;
  uint4 d[4][2];
  #pragma unroll
  for(int c=0;c<4;c++){
    const uint32_t tc = (lane>>3)+c, rho = c*8+((tc&3)<<1)+(lane&1), sl = (lane&6)+(tc>>2);
    lds128(eb+rho*128+(((rho+sl)&7)<<4), d[c][0].x,d[c][0].y,d[c][0].z,d[c][0].w);
    uint32_t ad = eb+rho*128+(((rho+sl+1)&7)<<4);
    if(c>0 && sl==7) ad = PART? sb+OFF_U+128*16 : x8+rho*16;
    lds128(ad, d[c][1].x,d[c][1].y,d[c][1].z,d[c][1].w);
  }
#define SUM4(K,F) hadd2_bf16(hadd2_bf16(d[0][K].F,d[1][K].F),hadd2_bf16(d[2][K].F,d[3][K].F))
  uint4 o0, o1;
  o0.x=hadd2_bf16(x[0].x,hmul2_bf16(a[0].x,SUM4(0,x))); o0.y=hadd2_bf16(x[0].y,hmul2_bf16(a[0].y,SUM4(0,y)));
  o0.z=hadd2_bf16(x[0].z,hmul2_bf16(a[0].z,SUM4(1,x))); o0.w=hadd2_bf16(x[0].w,hmul2_bf16(a[0].w,SUM4(1,y)));
  o1.x=hadd2_bf16(x[1].x,hmul2_bf16(a[1].x,SUM4(0,z))); o1.y=hadd2_bf16(x[1].y,hmul2_bf16(a[1].y,SUM4(0,w)));
  o1.z=hadd2_bf16(x[1].z,hmul2_bf16(a[1].z,SUM4(1,z))); o1.w=hadd2_bf16(x[1].w,hmul2_bf16(a[1].w,SUM4(1,w)));
  uint4* dst = (uint4*)(g_hT + (cb*4+chl)*2048 + (1-PART)*1024) + tw;
  const uint32_t par = lds32(sb+OFF_MISC)&1;
  if(PART==0){ o0.x=(o0.x&~1u)|par; o1.x=(o1.x&~1u)|par; }
  dst[0]=o0; dst[256]=o1;
}

__device__ __forceinline__ void first_x(const Maps& maps, uint32_t sb, int w, int delay){
  const int b = blockIdx.x, rank = b&1, rt = b>>3;
  const uint32_t bar = sb+OFF_BAR, xf = bar+8*(B_XFULL+w*NX), xd = sb+OFF_X+w*NX*XSLOT+rank*4096, rb = sb+(w? OFF_RES1:OFF_RES0);
  const int c0 = w*1024+rt*64, k0 = (rt>>1)+w*(SKW/2), cr = rank*256+((b>>1)&3)*64;
  mbar_expect_tx(xf, XSLOT); mbar_expect_tx(xf+8, XSLOT); mbar_expect_tx(xf+16, 2*XSLOT);
  if(delay){ mbar_wait(bar+8*(B_PH+1), 0); unsigned c0_, c1_; asm volatile("mov.u32 %0, %%clock;":"=r"(c0_)); do{ __nanosleep(40); asm volatile("mov.u32 %0, %%clock;":"=r"(c1_)); }while(c1_-c0_<(unsigned)delay); }
  tma2d_mc(xd,         &maps.ht, c0, (k0&7)*64+rank*32,     xf);
  tma2d_mc(xd+XSLOT,   &maps.ht, c0, ((k0+1)&7)*64+rank*32, xf+8);
  tma2d_mc(xd+2*XSLOT, &maps.ht, c0, ((k0+2)&7)*64+rank*32, xf+16);
  tma2d(rb,      &maps.ht, c0, cr,    xf+16);
  tma2d(rb+4096, &maps.ht, c0, cr+32, xf+16);
}

__global__ void __cluster_dims__(2,1,1) __launch_bounds__(384,1)
fused_kernel(const __grid_constant__ Maps maps, const bf16* __restrict__ q, const bf16* __restrict__ shk, const bf16* __restrict__ ssmk,
             const bf16* __restrict__ ssmD, const bf16* __restrict__ wgt, const bf16* __restrict__ wup, const bf16* __restrict__ wdn, bf16* __restrict__ out){
  extern __shared__ __align__(1024) uint8_t smem_raw[];
  unsigned c_begin; asm volatile("mov.u32 %0, %%clock;":"=r"(c_begin));
  const uint32_t sb = smem_u32(smem_raw);
  const int tid = threadIdx.x, lane = tid&31;
  const int warp = __shfl_sync(0xffffffffu, tid>>5, 0);
  const int wg = warp>>2;
  const int b = blockIdx.x, rank = b&1;
  const int f = b&7, rt = b>>3, fp = f>>1;
  const uint32_t bar = sb+OFF_BAR;

  if(wg==2){
    asm volatile("setmaxnreg.dec.sync.aligned.u32 " STR(RP) ";");
    STAMP(58);
    const int cg = CGMAP(b>>1);
    const int cb = cg*2+rank;
    unsigned epoch = 0; uint4 shw = make_uint4(0,0,0,0); uint2 dd = make_uint2(0,0);
    if(warp!=9){
      asm volatile("ld.relaxed.gpu.global.u32 %0, [%1];":"=r"(epoch):"l"(&g_cnt[warp==10? 64:32]));
      shw = ldg_nc128(shk + (cg*8+(lane&3)*2)*4);
      asm volatile("ld.global.nc.v2.u32 {%0,%1}, [%2];":"=r"(dd.x),"=r"(dd.y):"l"(ssmD + cb*4));
    }
    auto ldkv=[&](int i){
      const uint32_t fb=bar+8*(B_KV+i);
      mbar_expect_tx(fb, 2176+2048);
      tma3d(sb+KVOFF(i),      &maps.k, cg*8, i*32+rank*16-1, 0, fb);
      tma3d(sb+KVOFF(i)+2176, &maps.v, cg*8, i*32+rank*16,   0, fb);
    };
    if(warp==9){ if(lane<3) asm volatile("prefetch.tensormap [%0];"::"l"(&maps.k+lane):"memory"); }
    STAMP(51+warp);
    asm volatile("bar.sync 0;":::"memory");
    asm volatile("barrier.cluster.arrive.relaxed.aligned;":::"memory");
    if(warp==9){
      { unsigned c1; do{ asm volatile("mov.u32 %0, %%clock;":"=r"(c1)); }while(c1-c_begin<QDELAY); }
      if(elect_one()){
        mbar_expect_tx(bar+8*B_SK, 16384);
        bulk_g2s(sb+OFF_SK, ssmk+cb*4*2048, 16384, bar+8*B_SK);
        if(KDELAY>0){ unsigned c1; do{ asm volatile("mov.u32 %0, %%clock;":"=r"(c1)); }while(c1-c_begin<KDELAY); }
        #pragma unroll
        for(int i=0;i<KV0;i++) ldkv(i);
      }
      __syncwarp();
      mbar_wait(bar+8*B_QD, 0);
      STAMP(79);
      if(elect_one()){
        asm volatile("cp.async.bulk.tensor.2d.global.shared::cta.bulk_group [%0, {%1, %2}], [%3];"::"l"(&maps.xa),"r"(b*64),"r"(0),"r"(sb+OFF_IMG):"memory");
        asm volatile("cp.async.bulk.commit_group;":::"memory");
        #pragma unroll 1
        for(int i=KV0;i<8;i++){
          ldkv(i);
          if(i==XAFTER){
            asm volatile("cp.async.bulk.wait_group.read 0;":::"memory");
            mbar_wait(bar+8*(B_KV+XPOS), 0);
            mbar_expect_tx(bar+8*B_XA, 32768); bulk_g2s(sb+OFF_XAL, &g_xa[cb*1024], 16384, bar+8*B_XA); bulk_g2s(sb+OFF_XAE, g_qs, 16384, bar+8*B_XA);
            STAMP(66);
          }
        }
        mbar_wait(bar+8*(B_KV+WSTART), 0);
        #pragma unroll 1
        for(int it=0;it<W9;it++){
          mbar_wait(bar+8*(B_WEMPTY+it), 0);
          if(it>=PACE) mbar_wait(bar+8*(B_WFULL+it-PACE), 0);
          mbar_expect_tx(bar+8*(B_WFULL+it), 22528);
          load_w_stage(maps, sb+OFF_W+(5-it)*WSLOT, f*FS, ((it+(rt&14))&15)*32, bar+8*(B_WFULL+it));
          STAMP(24+it);
        }
      }
      __syncwarp();
    }
    asm volatile("":"+r"(epoch));
    epoch = (epoch>>7)+1;
    if(warp==11){
      if(lane<4) sts128(sb+OFF_ROW+lane*16, __byte_perm(shw.x,shw.z,0x5410), __byte_perm(shw.x,shw.z,0x7632), __byte_perm(shw.y,shw.w,0x5410), __byte_perm(shw.y,shw.w,0x7632));
      if(lane==0) sts128(sb+OFF_MISC, epoch, dd.x, dd.y, 0);
      __syncwarp();
      if(lane==0) mbar_arrive(bar+8*B_SC);
    }
    if(warp==8 && lane<5) asm volatile("prefetch.tensormap [%0];"::"l"(&maps.w64+lane):"memory");
    if(warp==9){ mbar_wait(bar+8*B_SC, 0); epoch = lds32(sb+OFF_MISC); }
    const uint32_t par = epoch&1;
    auto ldx=[&](int w, int it){
      const uint32_t fb = bar+8*(B_XFULL+w*NX+(it&3));
      mbar_expect_tx(fb, XSLOT);
      tma2d_mc(sb+OFF_X+(w*NX+(it&3))*XSLOT+rank*4096, &maps.ht, w*1024+rt*64, ((it+(rt>>1)+w*(SKW/2))&7)*64+rank*32, fb);
    };
    if(warp!=9){
      const int cp = lane&3;
      uint32_t sw[4];
      { const uint4 w = shw;
        sw[0]=__byte_perm(w.x,w.z,0x5410); sw[1]=__byte_perm(w.x,w.z,0x7632); sw[2]=__byte_perm(w.y,w.w,0x5410); sw[3]=__byte_perm(w.y,w.w,0x7632); }
      const uint32_t udst = mapa(sb+OFF_U+(cp&1)*2*UCH, cp>>1), ubar = mapa(bar+8*B_U, cp>>1);
      asm volatile("barrier.cluster.wait.aligned;":::"memory");
      #pragma unroll 1
      for(int tk=2*CP+(warp==8? 2:warp-10); tk<16; tk+=3){
        const int T=tk>>1, gl=(tk&1)*8+(lane>>2);
        mbar_wait(bar+8*(B_KV+T), 0);
        if(!(tk&1)) STAMP(8+T);
        const uint32_t ka = sb+KVOFF(T)+gl*16+cp*4, va = ka+2176;
        uint32_t kk[11], u[8];
        #pragma unroll
        for(int r=0;r<3;r++) kk[r]=lds32(ka+(5+r)*272);
        #pragma unroll
        for(int r=0;r<8;r++){ kk[3+r]=lds32(ka+16+r*272); u[r]=lds32(va+r*256); }
        #pragma unroll
        for(int r=0;r<8;r++){
          uint32_t a=hmul2_bf16(kk[r],sw[3]); a=hadd2_bf16(a,hmul2_bf16(kk[r+1],sw[2])); a=hadd2_bf16(a,hmul2_bf16(kk[r+2],sw[1])); a=hadd2_bf16(a,hmul2_bf16(kk[r+3],sw[0]));
          u[r]=hmul2_bf16(a,u[r]);
        }
        const int R = 255-(T*32+rank*16+gl);
        const uint32_t d = udst + (R&1)*UPL + (R>>1)*16;
        st_async128(d,     __byte_perm(u[7],u[6],0x5410), __byte_perm(u[5],u[4],0x5410), __byte_perm(u[3],u[2],0x5410), __byte_perm(u[1],u[0],0x5410), ubar+8*T);
        st_async128(d+UCH, __byte_perm(u[7],u[6],0x7632), __byte_perm(u[5],u[4],0x7632), __byte_perm(u[3],u[2],0x7632), __byte_perm(u[1],u[0],0x7632), ubar+8*T);
      }
      __syncwarp();
      if(lane==0) mbar_arrive(bar+8*B_TD);
    } else {
      asm volatile("barrier.cluster.wait.aligned;":::"memory");
    }
    if(warp==8){
      if(elect_one()){
        const int col = f*FS;
        #pragma unroll
        for(int it=W9; it<NS; it++){
          mbar_wait(bar+8*(B_WEMPTY+it), 0);
          if(it==3) mbar_wait(bar+8*B_TD, 0);
          if(it>=PACE) mbar_wait(bar+8*(B_WFULL+it-PACE), 0);
          mbar_expect_tx(bar+8*(B_WFULL+it), 22528);
          load_w_stage(maps, sb+OFF_W+(5-it)*WSLOT, col, ((it+(rt&14))&15)*32, bar+8*(B_WFULL+it));
          if(it<5) STAMP(24+it);
        }
        mbar_wait(bar+8*B_X03, 0); ldx(0,3);
        mbar_wait(bar+8*B_PK, 0);
        uint32_t wb = bar, dst = sb+OFF_W+5*WSLOT, ph = 1; int k0 = ((6+(rt&14))&15)*32;
        #pragma unroll 1
        for(int j=4; j<4+(10+SKW)/2; j++){
          mbar_wait(wb+8*B_WEMPTY, ph);
          mbar_expect_tx(wb, 22528);       load_w_stage(maps, dst, col, k0, wb);
          mbar_wait(wb+8*B_WEMPTY+8, ph);
          mbar_expect_tx(wb+8, 22528);     load_w_stage(maps, dst-WSLOT, col, k0+32, wb+8);
          if(j<8){ mbar_wait(bar+8*(B_XEMPTY+(j&3)), 0); ldx(0,j); }
          const int j1 = j-SKW/2;
          if(j1>=4 && j1<8){ if(j1==4) mbar_wait(bar+8*(B_FB+1), 0); mbar_wait(bar+8*(B_XEMPTY+NX+(j1&3)), 0); ldx(1,j1); }
          if(j==5) asm volatile("cp.async.bulk.prefetch.L2.global [%0], 11008;"::"l"(wdn+b*5504):"memory");
          const bool wrap = wb==bar+32;
          wb = wrap? bar : wb+16; dst = wrap? dst+4*WSLOT : dst-2*WSLOT; ph ^= wrap; k0 = (k0+64)&511;
        }
        #pragma unroll
        for(int j=0;j<8;j++){
          constexpr int I0=16+SKW;
          const int slot=(I0+j)%NS, ci=(G2_CH>>(4*j))&3, kh=((G2_PEER>>j)&1)^rank;
          mbar_wait(bar+8*(B_WEMPTY+slot), ((I0+j)/NS)&1);
          mbar_expect_tx(bar+8*(B_WFULL+slot), 22528);
          tma2d(sb+OFF_W+(5-slot)*WSLOT, &maps.wd, rank*256+((fp+ci)&3)*64, (2*fp+kh)*FS, bar+8*(B_WFULL+slot));
        }
      }
      __syncwarp();
    } else if(warp==11){
      mbar_wait(bar+8*B_INIT, 0);
      #pragma unroll 4
      for(int i=0;i<32;i++) ((uint4*)out)[b*1024+i*32+lane]=make_uint4(0,0,0,0);
      asm volatile("fence.proxy.async.global;":::"memory");
      __syncwarp();
      if(lane==0) mbar_arrive(bar+8*(B_HD+1));
      STAMP(30);
      mbar_wait(bar+8*(B_INIT+1), 0);
      __nanosleep(CSLEEP);
      STAMP(31);
      {
        const int j = rt*6+(lane>>2);
        float4 c = make_float4(0.f,0.f,0.f,0.f);
        if(lane<24 && j<88) c = gather_sum(&g_csp[(f*16+(lane&3)*4)*88+j], 4, 88, par);
        __syncwarp();
        #pragma unroll
        for(int o=1;o<4;o<<=1){ c.x+=__shfl_xor_sync(~0u,c.x,o); c.y+=__shfl_xor_sync(~0u,c.y,o); c.z+=__shfl_xor_sync(~0u,c.z,o); c.w+=__shfl_xor_sync(~0u,c.w,o); }
        if(lane<24 && j<88 && !(lane&3)) st_rlx128(&g_cs2[f*96+j], (__float_as_uint(c.x)&~1u)|par, __float_as_uint(c.y), __float_as_uint(c.z), __float_as_uint(c.w));
      }
      STAMP(29);
      { uint4 v[3]; int n=0; const int j2 = lane<24? lane+64 : lane;
        do{ __nanosleep(CSLEEP); ld_rlx128(&g_cs2[f*96+lane], v[0]); ld_rlx128(&g_cs2[f*96+lane+32], v[1]); ld_rlx128(&g_cs2[f*96+j2], v[2]); spin_guard(++n); }while(((v[0].x^par)|(v[1].x^par)|(v[2].x^par))&1);
        *(uint4*)(smem_raw+OFF_CS+lane*16)=v[0]; *(uint4*)(smem_raw+OFF_CS+(lane+32)*16)=v[1]; *(uint4*)(smem_raw+OFF_CS+j2*16)=v[2]; }
      mbar_wait(bar+8*(B_FB+1), 0);
      __syncwarp();
      if(lane<2) mbar_arrive(bar+8*(B_PAR+lane));
      STAMP(74);
      #pragma unroll 4
      for(int i=0;i<32;i++) g_xa[cb*1024+i*32+lane]=make_uint4(0,0,0,0);
    } else {
      const int w = warp-9;
      mbar_wait(bar+8*(B_HD+w), 0);
      STAMP(67+w*3);
      if(elect_one()){
        signal_add(&g_cnt[32+32*w]); STAMP(68+w*3);
        if(!w) mbar_arrive(bar+8*B_INIT);
        unsigned v; int n=0; do{ asm volatile("ld.acquire.gpu.global.u32 %0, [%1];":"=r"(v):"l"(&g_cnt[32+32*w]):"memory"); spin_guard(++n); }while((int)(v-epoch*128)<0);
        STAMP(7+w*16);
        asm volatile("fence.proxy.async.global;":::"memory");
        if(w) ldx(1,3); else { first_x(maps, sb, 0, 0); mbar_arrive(bar+8*B_X03); STAMP(63); }
        mbar_arrive(bar+8*(B_FB+w));
      }
      __syncwarp();
      mbar_wait(bar+8*(B_XEMPTY+w*NX+STX), 0);
      {
        __nanosleep(CSLEEP);
        const float4 st=gather_sum(&g_stat[((rt*2+w)*8)*32+lane], 8, 32, par);
        const float s0=st.x, q0=st.y, s1=st.z, q1=st.w;
        const float m0=s0*(1.f/512), m1=s1*(1.f/512);
        const float v0=fmaxf(q0*(1.f/512)-m0*m0,0.f), v1=fmaxf(q1*(1.f/512)-m1*m1,0.f);
        const float r0=ln_rstd(v0), r1=ln_rstd(v1);
        *(float4*)(smem_raw+OFF_ROW+w*512+lane*16)=make_float4(-rbf(m0),r0,-rbf(m1),r1);
        __syncwarp();
        if(lane==0) mbar_arrive(bar+8*(B_PAR+w));
        STAMP(75+w);
      }
      STAMP(77+w);
    }
  } else {
    if(elect_one()){
      mbar_init(bar+8*(B_Q+warp),1);
      asm volatile("fence.proxy.async.shared::cta;":::"memory");
      mbar_expect_tx(bar+8*(B_Q+warp), 2048);
      const bf16* qp = q + pos2row((1-wg)*1024+b*8+(warp&3)*2)*512;
      bulk_g2s(sb+OFF_Q+2*warp*QP, qp, 1024, bar+8*(B_Q+warp)); bulk_g2s(sb+OFF_Q+(2*warp+1)*QP, qp-16*512, 1024, bar+8*(B_Q+warp));
    }
    __syncwarp();
    asm volatile("setmaxnreg.inc.sync.aligned.u32 " STR(RC) ";");
    if(elect_one()){
      mbar_init(bar+8*(B_U+warp),1); mbar_expect_tx(bar+8*(B_U+warp), 2048);
      mbar_init(bar+8*(B_XFULL+warp),1); mbar_init(bar+8*(B_XEMPTY+warp),8);
      mbar_init(bar+8*(B_KV+warp),1);
      if(warp<NS){ mbar_init(bar+8*(B_WFULL+warp),1); mbar_init(bar+8*(B_WEMPTY+warp),8); mbar_init(bar+8*(B_ONE+warp),1); }
      else { const int i=warp-6; mbar_init(bar+8*(B_PRDY+i),4); mbar_init(bar+8*(B_PH+i),16); mbar_init(bar+8*(B_RT+i),1); mbar_init(bar+8*(B_AFULL+i),1); mbar_expect_tx(bar+8*(B_AFULL+i), 22528); mbar_init(bar+8*(B_PAR+i),2); mbar_init(bar+8*(B_HD+i),8+i); if(i){ mbar_init(bar+8*B_SK,1); mbar_init(bar+8*B_SC,1); mbar_init(bar+8*B_X03,9); } else { mbar_init(bar+8*B_QD,8); mbar_init(bar+8*B_PK,3); mbar_init(bar+8*B_TD,3); } }
      asm volatile("fence.mbarrier_init.release.cluster;":::"memory");
    }
    __syncwarp();
    STAMP(56);
    const int wq = warp&3, g = lane>>2, t = lane&3;
    if(tid<8){ sts128(sb+OFF_U+tid*UPL+128*16, 0,0,0,0); }
    if(tid<12){ sts128(sb+OFF_TBL+(tid&3)*TBL+(tid>>2)*16, 0,0,0,0); }
    asm volatile("bar.sync 0;":::"memory");
    asm volatile("barrier.cluster.arrive.relaxed.aligned;":::"memory");
    STAMP(57);
    #pragma unroll
    for(int i=0;i<4;i++) mbar_wait(bar+8*(B_Q+wg*4+i), 0);
    STAMP(92+wg);
    {
      const uint32_t la = sb+OFF_Q+(wg*8+2*(lane>>3)+(lane&1))*QP + ((lane&7)>>1)*16 + wq*256;
      uint4 tv[4]; uint32_t w[2][8];
      const int irow = wq*32+t*2+(g>>2);
      const uint32_t dst = sb+OFF_IMG+irow*128+(((((g&3)+4*wg)^(b&7))^(irow&7))<<4);
      #pragma unroll
      for(int i=0;i<4;i++) ldsm4t(la+i*64, tv[i].x,tv[i].y,tv[i].z,tv[i].w);
      #pragma unroll
      for(int i=0;i<4;i++) sts128(dst+i*1024, max(~tv[i].x,1u),tv[i].y,tv[i].z,tv[i].w);
      asm volatile("fence.proxy.async.shared::cta;":::"memory");
      __syncwarp();
      if(lane==0) mbar_arrive(bar+8*B_QD);
      if(wg==0) STAMP(44);
      const uint32_t qa = sb+OFF_Q+(2*warp)*QP+lane*16;
      #pragma unroll
      for(int r=0;r<2;r++){ lds128_nm(qa+r*QP, w[r][0],w[r][1],w[r][2],w[r][3]); lds128_nm(qa+r*QP+512, w[r][4],w[r][5],w[r][6],w[r][7]); }
      float s[2], d[2];
      #pragma unroll
      for(int r=0;r<2;r++){
        float s0=0.f,s1=0.f,d0=0.f,d1=0.f;
        #pragma unroll
        for(int i=0;i<8;i++){ const float lo=bf_lo(w[r][i]), hi=bf_hi(w[r][i]); s0+=lo; s1+=hi; d0=fmaf(lo,lo,d0); d1=fmaf(hi,hi,d1); }
        s[r]=s0+s1; d[r]=d0+d1;
      }
      const bool u=lane&16, v=lane&8;
      const float a0=(u? s[1]:s[0])+__shfl_xor_sync(~0u,u? s[0]:s[1],16), a1=(u? d[1]:d[0])+__shfl_xor_sync(~0u,u? d[0]:d[1],16);
      float c0=(v? a1:a0)+__shfl_xor_sync(~0u,v? a0:a1,8);
      c0+=__shfl_xor_sync(~0u,c0,4); c0+=__shfl_xor_sync(~0u,c0,2); c0+=__shfl_xor_sync(~0u,c0,1);
      const float m=c0*(1.f/512), sq=__shfl_down_sync(~0u,c0,8);
      const float rs=ln_rstd(fmaxf(fmaf(-m,m,sq*(1.f/512)),0.f)), rh=rbf(rs);
      const float m1=__shfl_down_sync(~0u,m,16), rs1=__shfl_down_sync(~0u,rs,16), rh1=rbf(rs1);
      mbar_wait(bar+8*B_SC, 0);
      if(lane==0){ st_rlx128(&g_qs[b*8+(warp^(b&7))], pack_bf16(m,m1), pack_bf16(rh,rh1), pack_bf16(rs-rh,rs1-rh1), lds32(sb+OFF_MISC)); }
      __syncwarp();
      if(wg==0) STAMP(46);
    }
    mbar_wait(bar+8*B_SK, 0);
    STAMP(90+wg);
    {
      const int Q = tid+2;
      const uint32_t ta = sb+OFF_TBL+((Q*32)^(((Q>>2)&3)<<5));
      const bool sw2 = (Q>>2)&1;
      uint4 kq[4]; uint32_t kn[4];
      #pragma unroll
      for(int i=0;i<4;i++){ lds128_nm(sb+OFF_SK+i*4096+tid*16, kq[i].x,kq[i].y,kq[i].z,kq[i].w); kn[i] = lds32(sb+OFF_SK+i*4096+(warp+1)*512); }
      if(tid==0){
        const uint32_t d01=lds32(sb+OFF_MISC+4), d23=lds32(sb+OFF_MISC+8);
        kq[0].x=hadd2_bf16(kq[0].x,d01&0xffffu); kq[1].x=hadd2_bf16(kq[1].x,d01>>16); kq[2].x=hadd2_bf16(kq[2].x,d23&0xffffu); kq[3].x=hadd2_bf16(kq[3].x,d23>>16);
      }
      __syncwarp();
      #pragma unroll
      for(int i=0;i<4;i++){
        uint32_t nx = __shfl_down_sync(~0u, kq[i].x, 1); if(lane==31) nx = kn[i];
        const uint4 o = make_uint4(__byte_perm(kq[i].x,kq[i].y,0x5432), __byte_perm(kq[i].y,kq[i].z,0x5432), __byte_perm(kq[i].z,kq[i].w,0x5432), __byte_perm(kq[i].w,nx,0x5432));
        const uint4 f0 = sw2? o:kq[i], f1 = sw2? kq[i]:o;
        sts128(ta+i*TBL+(sw2?16:0), f0.x,f0.y,f0.z,f0.w);
        sts128(ta+i*TBL+(sw2?0:16), f1.x,f1.y,f1.z,f1.w);
        if(tid==0) sts128(sb+OFF_TBL+i*TBL+48, 0,0,0, kq[i].x<<16);
      }
      __syncwarp();
      if(lane<4 && lane!=2) mbar_arrive(bar+8*(B_WEMPTY+lane));
      asm volatile("bar.sync 1, 256;":::"memory");
    }
    STAMP(80+wg);
    STAMP(82+wg);
    asm volatile("barrier.cluster.wait.aligned;":::"memory");
    {
      const int c=lane>>3, p=g&1;
      uint32_t tb[5];
      #pragma unroll
      for(int s=0;s<5;s++){ const int y=16*c+wq+t+p+4*s; const int id=8*(y>>2)+4*(1-p)+(y&3); tb[s]=sb+OFF_TBL+wg*2*TBL+((id^(((id>>5)&3)<<3))<<2); }
      uint64_t du = make_desc(sb+OFF_U+wg*2*UCH, UPL, 128, 0);
      float aE[2][32], aL[2][32];
      uint32_t R[2][4][8]; uint4 xr[2], ar[2];
#define P_TY(K) ((K)>=8 ? 2 : (K)&1)
#define P_LV(K) ((K)>=8 ? (K)-8 : (K)>>1)
#define P_MA(K) ((P_TY(K)==1 ? 15 : 7) - 2*P_LV(K))
#define P_N(K,M) (P_TY(K)==2 ? 64 : P_TY(K)==1 ? 128-8*(M) : 64-8*(M))
#define P_B(K,M) (8*(M) + (P_TY(K)==0 ? 64 : 0))
#define P_LD(K,J) conv_lda(R[(K)&1][J],tb,((J)&1)*TBL+(P_MA(K)-((J)>>1))*512)
#define P_MMA(K,J) conv_mma<P_N(K,P_MA(K)-((J)>>1))>(P_TY(K)==0? aE[(J)&1]:aL[(J)&1], R[(K)&1][J], du+((J)&1)*(UCH/16)+P_B(K,P_MA(K)-((J)>>1)))
      const uint32_t kva = sb+OFF_KV+(warp*2+p)*16+t*4, udst = mapa(sb+OFF_U+((t&1)*2+(c&1))*UCH, t>>1), ubar = mapa(bar+8*B_U, t>>1);
      uint32_t ko[5];
      #pragma unroll
      for(int r=0;r<5;r++){ const int row=2*c-3+r; ko[r]=kva+(row&7)*272+(row<0?0:16); }
#define KV_PREP(T) if constexpr(T<CP){ mbar_wait(bar+8*(B_KV+T),0); if(wg==0) STAMP(8+T); uint32_t k_[5], w0,w1,w2,w3; lds128_nm(sb+OFF_ROW+t*16, w0,w1,w2,w3); \
        _Pragma("unroll") for(int r=0;r<5;r++) k_[r]=lds32(ko[r]+T*KVCH); \
        uint32_t u0=lds32(kva+T*KVCH+2176+c*512), u1=lds32(kva+T*KVCH+2176+c*512+256); \
        u0=hmul2_bf16(hadd2_bf16(hadd2_bf16(hadd2_bf16(hmul2_bf16(k_[0],w3),hmul2_bf16(k_[1],w2)),hmul2_bf16(k_[2],w1)),hmul2_bf16(k_[3],w0)),u0); \
        u1=hmul2_bf16(hadd2_bf16(hadd2_bf16(hadd2_bf16(hmul2_bf16(k_[1],w3),hmul2_bf16(k_[2],w2)),hmul2_bf16(k_[3],w1)),hmul2_bf16(k_[4],w0)),u1); \
        const uint32_t kp_=__byte_perm(u1,u0,(c&1)?0x7632:0x5410), rc_=__shfl_xor_sync(~0u,__byte_perm(u1,u0,(c&1)?0x5410:0x7632),8); \
        const uint32_t lo_=(c&1)? rc_:kp_, hi_=(c&1)? kp_:rc_;     \
        const uint32_t l2_=__shfl_xor_sync(~0u,lo_,16), h2_=__shfl_xor_sync(~0u,hi_,16); \
        const int R_=255-(T*32+rank*16+warp*2+p); \
        if(c<2) st_async128(udst+(R_&1)*UPL+(R_>>1)*16, h2_, l2_, hi_, lo_, ubar+8*T); }
#define CONV_PREP(K) { P_LD(K,0); P_LD(K,1); P_LD(K,2); P_LD(K,3); }
#define CONV_PAIR(K) { \
        _Pragma("unroll") for(int j=0;j<4;j++) conv_dup(R[(K)&1][j]); \
        if constexpr(P_TY(K)<2){ _Pragma("unroll") for(int i=0;i<2;i++){ float* a_=(P_TY(K)==0? aE[i]:aL[i])+8*P_LV(K); zero4(a_); zero4(a_+4); } } \
        if constexpr(P_TY(K)!=1){ mbar_wait(bar+8*(B_U+P_LV(K)+(P_TY(K)?4:0)),0); if constexpr(P_TY(K)==2 || PFE) asm volatile("fence.proxy.async.shared::cta;":::"memory"); } \
        asm volatile("" : "+l"(du)); \
        PP_SYNC(); \
        if constexpr((K)==0||(K)==6||(K)==7||(K)==11){ if(wg==0) STAMP(96+(K)); } \
        wg_fence(); \
        P_MMA(K,0); P_MMA(K,1); \
        if constexpr(P_TY(K)<2){ wg_commit(); wg_fence(); } \
        P_MMA(K,2); P_MMA(K,3); \
        wg_commit(); \
        if((K)<11 || wg==0) PP_ARRIVE(); \
        if constexpr((K)<11){ if constexpr((K)>0){ if constexpr(P_TY(K)<2) wg_wait<2>(); else wg_wait<1>(); } if constexpr((K)!=KEPI || (K)==6) CONV_PREP((K)+1) } }
#define PP_SYNC() asm volatile("bar.sync %0, 256;"::"r"(2+wg):"memory")
#define PP_ARRIVE() asm volatile("bar.arrive %0, 256;"::"r"(3-wg):"memory")
      if(wg==1) PP_ARRIVE();
      KV_PREP(0) CONV_PREP(0) KV_PREP(1) CONV_PAIR(0) CONV_PAIR(1) KV_PREP(2) CONV_PAIR(2) CONV_PAIR(3) KV_PREP(3) CONV_PAIR(4) CONV_PAIR(5)
      if(XEARLY){ if(wg==0) STAMP(100); mbar_wait(bar+8*B_XA,0); if(wg==0) STAMP(101); load_xa<1>(xr,ar,sb,warp,lane); }
      CONV_PAIR(6)
      if(lane==0) mbar_arrive(bar+8*(B_WEMPTY+2));
#define CONV_EPIE(K) if constexpr((K)==KEPI){ if(!XEARLY){ mbar_wait(bar+8*B_XA,0); load_xa<1>(xr,ar,sb,warp,lane); } if constexpr((K)==6) wg_wait<0>(); conv_put<1>(aE[0],aE[1],sb,warp,lane); \
        conv_get<1>(xr,ar,sb,warp,lane); __syncwarp(); if(lane==0) mbar_arrive(bar+8*B_HD); STAMP(84+wg); if constexpr((K)!=6) CONV_PREP((K)+1) } \
      if constexpr((K)==KEPI+1){ load_xa<0>(xr,ar,sb,warp,lane); if(lane==0) mbar_arrive(bar+8*(B_WEMPTY+4)); }
      CONV_EPIE(6)
      CONV_PAIR(7) CONV_EPIE(7)
      CONV_PAIR(8) CONV_EPIE(8)
      CONV_PAIR(9) CONV_EPIE(9)
      CONV_PAIR(10)
      CONV_PAIR(11)
      wg_wait<0>();
      STAMP(86+wg);
      conv_put<0>(aL[0],aL[1],sb,warp,lane);
      conv_get<0>(xr,ar,sb,warp,lane);
      __syncwarp();
      if(lane==0){ mbar_arrive(bar+8*(B_HD+1)); mbar_arrive(bar+8*(B_WEMPTY+5)); }
      if(lane<2){ mbar_arrive_cl(mapa(bar+8*(B_PH+1), lane)); if(wg==0) mbar_arrive_cl(mapa(bar+8*B_X03, lane)); }
      STAMP(88+wg);
    }
    if(wg==1 && wq<3){
      mbar_wait(bar+8*(B_WFULL+(rt&1)), 0);
      const int j = tid-128;
      const uint32_t par = lds32(sb+OFF_MISC)&1;
      float c0=0.f,c1=0.f,c2=0.f,c3=0.f;
      const uint32_t cb = sb+OFF_W+(5-(rt&1))*WSLOT+wq*8192+t*4+maps.upfirst*4096;
      #pragma unroll 8
      for(int k=0;k<32;k++){
        const uint32_t ad = cb + k*128 + ((g^(k&7))<<4);
        const uint32_t v=lds32(ad), u=lds32(ad+4096-maps.upfirst*8192); c0+=bf_lo(v); c1+=bf_hi(v); c2+=bf_lo(u); c3+=bf_hi(u);
      }
      if(j<88) st_rlx128(&g_csp[(f*16+rt)*88+j], (__float_as_uint(c0)&~1u)|par, __float_as_uint(c1), __float_as_uint(c2), __float_as_uint(c3));
      __syncwarp();
      if(lane==0) mbar_arrive(bar+8*B_PK);
    }
    if(warp==7){ if(elect_one()){ first_x(maps, sb, 1, ODL); mbar_arrive(bar+8*(B_INIT+1)); } __syncwarp(); STAMP(94); }
    const uint32_t xempty_cl = mapa(bar+8*(B_XEMPTY+wg*NX), lane&1);
    float ag[88], au[88];
    const uint32_t xbase = sb+OFF_X+wg*NX*XSLOT, rbase = sb+(wg? OFF_RES1:OFF_RES0);
    const uint32_t rfrag = rbase+((lane&7)+8*(lane>>4))*128+(((2*wq+((lane>>3)&1))^(lane&7))<<4);
    constexpr uint64_t DHI_A = (uint64_t)0x40000040u<<32, DHI_B = DHI_A | (512u<<16);
    const uint32_t og = maps.upfirst*256, ou = 256-og;
    uint32_t wb = bar+8*wg*(SKW%NS), ph = wg*(SKW/NS), dbl = (((sb+OFF_W+(5-wg*(SKW%NS))*WSLOT)&0x3FFFF)>>4), dal = (xbase&0x3FFFF)>>4, xb = bar+8*(B_XFULL+wg*NX), pwb = 0;
    uint32_t relm = lane==0? 0xff : lane==1? (wg? (0xff00>>(SKW/2))&0xff : (1<<(SKW/2))-1) : 0;
#define G1_STAGE(DA,DB,ACC) { wg_fence(); wgmma_ss<176,1,1>(ag, DA, DHI_B|((DB)+og), ACC); wgmma_ss<176,1,1>(au, DA, DHI_B|((DB)+ou), ACC); wgmma_ss<176,1,1>(ag, (DA)+128, DHI_B|((DB)+og+128), 1); wgmma_ss<176,1,1>(au, (DA)+128, DHI_B|((DB)+ou+128), 1); wg_commit(); }
    {
      mbar_wait(wb, ph); mbar_wait(xb, 0);
      if(wg==1){ mbar_wait(xb+8, 0); mbar_wait(xb+16, 0);
        STAMP(47);
        const uint32_t par = lds32(sb+OFF_MISC);
        #pragma unroll 1
        for(int n=0;n<100000;n++){
          uint32_t bad=0;
          #pragma unroll
          for(int i=0;i<8;i++) bad |= lds32((i<6? xbase+i*4096 : rbase+(i-6)*4096)+(tid&127)*32+((tid>>2)&1)*16)^par;
          uint32_t any;
          asm volatile("{ .reg .pred p,q; setp.ne.u32 p, %1, 0; barrier.cta.red.or.pred q, %2, 128, p; selp.u32 %0,1,0,q; }":"=r"(any):"r"(bad&1),"r"(4+wg):"memory");
          if(!__any_sync(~0u, any)) break;
          if(wq==0 && elect_one()){
            mbar_expect_tx(bar+8*(B_RT+wg), 4*XSLOT);
            #pragma unroll 1
            for(int i=0;i<8;i++) tma2d(i<6? xbase+i*4096 : rbase+(i-6)*4096, &maps.ht, wg*1024+rt*64, (i<6? ((rt>>1)+wg*(SKW/2)+(i>>1))&7 : rank*4+fp)*64+(i&1)*32, bar+8*(B_RT+wg));
          }
          __syncwarp();
          mbar_wait(bar+8*(B_RT+wg), n&1);
        } }
      STAMP(1+wg*16);
      #pragma unroll
      for(int i=0;i<88;i++){ ag[i]=0.f; au[i]=0.f; }
      G1_STAGE(DHI_A|dal, dbl, 0)
    }
    uint32_t okb = mbar_test(wb+8, ph);
    #pragma unroll 1
    for(int xi=0; xi<8; xi++){
      if(!okb) mbar_wait(wb+8, ph);
      G1_STAGE(DHI_A|(dal+256), dbl-WSLOT/16, 1)
      pwb = wb;
      const bool wrap = wb==bar+8*4;
      wb = wrap? bar : wb+16; dbl = wrap? dbl+4*(WSLOT/16) : dbl-2*(WSLOT/16); ph ^= wrap;
      dal = (xi==3)? dal-3*512 : dal+512; xb = (xi==3)? xb-24 : xb+8;
      const uint32_t oka = mbar_test(xb, xi>=3) & mbar_test(wb, ph);
      if(xi==STX){
        mbar_wait(bar+8*(B_XFULL+wg*NX+2), 0);
        float s0=0.f,s1=0.f,q0=0.f,q1=0.f;
        #pragma unroll
        for(int kk=0;kk<4;kk++){
          uint32_t r[4]; ldsm4t(rfrag+kk*2048, r[0],r[1],r[2],r[3]);
          #pragma unroll
          for(int i=0;i<4;i++){ const float lo=bf_lo(r[i]), hi=bf_hi(r[i]); if(i&1){ s1+=lo+hi; q1=fmaf(lo,lo,fmaf(hi,hi,q1)); } else { s0+=lo+hi; q0=fmaf(lo,lo,fmaf(hi,hi,q0)); } }
        }
        #pragma unroll
        for(int o=1;o<4;o<<=1){ s0+=__shfl_xor_sync(~0u,s0,o); q0+=__shfl_xor_sync(~0u,q0,o); s1+=__shfl_xor_sync(~0u,s1,o); q1+=__shfl_xor_sync(~0u,q1,o); }
        if(t==0) st_rlx128(&g_stat[((rt*2+wg)*8+f)*32+wq*8+g], (__float_as_uint(s0)&~1u)|(lds32(sb+OFF_MISC)&1), __float_as_uint(q0), __float_as_uint(s1), __float_as_uint(q1));
        __syncwarp();
      }
      uint32_t rel = relm&1; relm>>=1; uint32_t xpar = xi>=3;
      asm volatile("":"+r"(rel),"+r"(xpar));
      wg_wait<1>();
      if(rel) mbar_arrive(pwb+8*B_WEMPTY);
      if(xi==7) break;
      if(!oka){ mbar_wait(xb, xpar); mbar_wait(wb, ph); }
      if(LD2>0 && wg==1 && xi==7-SKW/2-LD2) asm volatile("bar.sync 1, 256;":::"memory");
      G1_STAGE(DHI_A|dal, dbl, 1)
      okb = mbar_test(wb+8, ph);
      wg_wait<1>();
      if(rel) mbar_arrive(pwb+8*B_WEMPTY+8);
      if((lane>>1)==1) mbar_arrive_cl(xempty_cl+8*(xi&3));
    }
    if(LD2>0 && wg==0) asm volatile("bar.arrive 1, 256;":::"memory");
    mbar_wait(bar+8*(B_PAR+wg), 0);
    const float4 p0=*(const float4*)(smem_raw+OFF_ROW+(wg*32+wq*8+g)*16);
    const float nm0=p0.x, r0=p0.y, nm1=p0.z, r1=p0.w;
    wg_wait<0>();
    STAMP(2+wg*16);
    if(lane==0){ mbar_arrive_n(pwb+8*B_WEMPTY+8, (wg && SKW)? 2:1); mbar_arrive_cl(mapa(bar+8*(B_PRDY+wg), rank^1)); }
    uint32_t act[44], actp[44];
    const float sc0=0.5f*r0*r0, sc1=0.5f*r1*r1;
    const uint32_t adst = mapa(xbase+wq*8192+lane*16, rank^1), abar = mapa(bar+8*(B_AFULL+wg), rank^1);
    {
      const float4* cs = (const float4*)(smem_raw+OFF_CS);
      const float h0=0.5f*r0, h1=0.5f*r1;
      mbar_wait(bar+8*(B_PRDY+wg), 0);
      #pragma unroll
      for(int j=0;j<22;j++){
        const float4 c4=cs[4*j+t];
        const float g0=fmaf(nm0,c4.x,ag[4*j+0]), g1=fmaf(nm0,c4.y,ag[4*j+1]), g2=fmaf(nm1,c4.x,ag[4*j+2]), g3=fmaf(nm1,c4.y,ag[4*j+3]);
        const float y0=g0*fmaf(nm0,c4.z,au[4*j+0]), y1=g1*fmaf(nm0,c4.w,au[4*j+1]), y2=g2*fmaf(nm1,c4.z,au[4*j+2]), y3=g3*fmaf(nm1,c4.w,au[4*j+3]);
        act[2*j]  =pack_bf16(fmaf(y0,tanh_fast(g0*h0),y0), fmaf(y1,tanh_fast(g1*h0),y1));
        act[2*j+1]=pack_bf16(fmaf(y2,tanh_fast(g2*h1),y2), fmaf(y3,tanh_fast(g3*h1),y3));
        if(NIN>5? ((j%3)==2 && j/3<NIN) : ((j&3)==3 && (j>>2)<NIN)){ const int kk=NIN>5? j/3 : j>>2; st_async128(adst+kk*512, act[4*kk],act[4*kk+1],act[4*kk+2],act[4*kk+3], abar); }
      }
    }
    STAMP(3+wg*16);
    if(wg==1 || !SEND0){
      #pragma unroll
      for(int kk=NIN;kk<11;kk++) st_async128(adst+kk*512, act[4*kk],act[4*kk+1],act[4*kk+2],act[4*kk+3], abar);
    }
    float acc2[2][32];
    #pragma unroll
    for(int i=0;i<32;i++){ acc2[0][i]=0.f; acc2[1][i]=0.f; }
    const uint32_t wbase = xbase+wq*8192;
    const uint32_t srow = ((~lane&4)<<1) | ((~lane&1)<<2) | (lane&2) | ((lane>>3)&1);
    const int orow = pos2row(wg*1024+rt*64+wq*16+5);
    uint32_t hr[16];
    #pragma unroll
    for(int kk=0;kk<4;kk++) ldsm4t(rfrag+kk*2048, hr[4*kk],hr[4*kk+1],hr[4*kk+2],hr[4*kk+3]);
    auto stage=[&](const float* a, int c){
      #pragma unroll
      for(int kk=0;kk<4;kk++){
        uint32_t o0=pack_bf16(a[8*kk]*sc0,a[8*kk+1]*sc0), o1=pack_bf16(a[8*kk+2]*sc1,a[8*kk+3]*sc1), o2=pack_bf16(a[8*kk+4]*sc0,a[8*kk+5]*sc0), o3=pack_bf16(a[8*kk+6]*sc1,a[8*kk+7]*sc1);
        if(c==0){
          o0=hadd2_bf16(o0,hr[4*kk]); o1=hadd2_bf16(o1,hr[4*kk+1]); o2=hadd2_bf16(o2,hr[4*kk+2]); o3=hadd2_bf16(o3,hr[4*kk+3]);
        }
        stsm4_nm(wbase+c*2048+srow*128+(((2*kk+(lane>>4))^(srow&7))<<4), o0,o1,o2,o3);
      }
    };
    auto flush=[&](int c, int n){
      asm volatile("fence.proxy.async.shared::cta;":::"memory");
      __syncwarp();
      if(elect_one()){
        #pragma unroll
        for(int i=0;i<n;i++) tma4d_red_add(&maps.out, rank*256+((fp+c+i)&3)*64, orow&7, (orow>>3)&15, orow>>7, wbase+(c+i)*2048);
        asm volatile("cp.async.bulk.commit_group;":::"memory");
      }
    };
    uint32_t okw = 0;
    #pragma unroll
    for(int i=0;i<8;i++){
      const int ch = (G2_CH>>(4*i))&3, peer = (G2_PEER>>i)&1;
      constexpr int S0=(16+SKW)%NS, P0=((16+SKW)/NS)&1;
      const int slot=(S0+i)%NS, pslot=(S0+i+NS-1)%NS, ph=(P0+(S0+i)/NS)&1;
      if(i==2){
        mbar_wait(bar+8*(B_AFULL+wg), 0);
        #pragma unroll
        for(int kk=0;kk<11;kk++) lds128_nm(wbase+lane*16+kk*512, actp[4*kk],actp[4*kk+1],actp[4*kk+2],actp[4*kk+3]);
      }
      if(!okw) mbar_wait(bar+8*(B_WFULL+slot), ph);
      if(i<7) okw = mbar_test(bar+8*(B_WFULL+(S0+i+1)%NS), (P0+(S0+i+1)/NS)&1);
      if(i==4 || (i==6 && wg==0) || ((i==0 || i==2) && wg==1)) asm volatile("bar.sync %0, 256;"::"r"(2+wg):"memory");
      const uint64_t db = make_desc(sb+OFF_W+(5-slot)*WSLOT, 0, 1024, 1);
      wg_fence();
      #pragma unroll
      for(int kk=0;kk<11;kk++){
        if(peer) wgmma_rs<64,1>(acc2[ch&1], actp[4*kk],actp[4*kk+1],actp[4*kk+2],actp[4*kk+3], db+kk*128, 1);
        else     wgmma_rs<64,1>(acc2[ch&1], act[4*kk],act[4*kk+1],act[4*kk+2],act[4*kk+3], db+kk*128, kk>0);
      }
      wg_commit();
      if(SEND0 && i==0 && wg==0){
        #pragma unroll
        for(int kk=NIN;kk<11;kk++) st_async128(adst+kk*512, act[4*kk],act[4*kk+1],act[4*kk+2],act[4*kk+3], abar);
      }
      if(i==3 || (i==1 && wg==1) || ((i==5 || i==7) && wg==0)) asm volatile("bar.arrive %0, 256;"::"r"(3-wg):"memory");
      if(i==1 && wg==1){ wg_wait<0>(); if(lane<4) mbar_arrive(bar+8*(B_WEMPTY+((lane&1)? slot:pslot))); }
      if(i==3){ wg_wait<1>(); stage(acc2[0], 0); flush(0,1); wg_wait<0>(); stage(acc2[1], 1); flush(1,1); }
      if(i==5 && wg==0){ wg_wait<0>(); stage(acc2[0], 2); flush(2,1); }
      STAMP(32+wg*16+i);
    }
    if(wg==1){ wg_wait<2>(); stage(acc2[0], 2); flush(2,1); }
    wg_wait<0>();
    STAMP(4+wg*16);
    stage(acc2[1], 3); flush(3,1);
    STAMP(5+wg*16);
    asm volatile("cp.async.bulk.wait_group.read 0;":::"memory");
    STAMP(6+wg*16);
  }
  __syncwarp();
  asm volatile("barrier.cluster.arrive.relaxed.aligned;":::"memory");
  asm volatile("barrier.cluster.wait.aligned;":::"memory");
}

typedef CUresult (*PFN_encodeTiled)(CUtensorMap*, CUtensorMapDataType, cuuint32_t, void*, const cuuint64_t*, const cuuint64_t*, const cuuint32_t*, const cuuint32_t*, CUtensorMapInterleave, CUtensorMapSwizzle, CUtensorMapL2promotion, CUtensorMapFloatOOBfill);
static void make2d(PFN_encodeTiled enc, CUtensorMap* m, const void* p, uint64_t d0, uint64_t d1, uint32_t b0, uint32_t b1){
  cuuint64_t gd[2]={d0,d1}; cuuint64_t gs[1]={d0*2}; cuuint32_t bx[2]={b0,b1}; cuuint32_t es[2]={1,1};
  enc(m,CU_TENSOR_MAP_DATA_TYPE_BFLOAT16,2,(void*)p,gd,gs,bx,es,CU_TENSOR_MAP_INTERLEAVE_NONE,CU_TENSOR_MAP_SWIZZLE_128B,CU_TENSOR_MAP_L2_PROMOTION_L2_128B,CU_TENSOR_MAP_FLOAT_OOB_FILL_NONE);
}
static void make3d(PFN_encodeTiled enc, CUtensorMap* m, const void* p, uint64_t d0, uint64_t d1, uint64_t d2, uint64_t s1, uint64_t s2, uint32_t b0, uint32_t b1, uint32_t b2, CUtensorMapSwizzle sw, CUtensorMapL2promotion pr){
  cuuint64_t gd[3]={d0,d1,d2}; cuuint64_t gs[2]={s1,s2}; cuuint32_t bx[3]={b0,b1,b2}; cuuint32_t es[3]={1,1,1};
  enc(m,CU_TENSOR_MAP_DATA_TYPE_BFLOAT16,3,(void*)p,gd,gs,bx,es,CU_TENSOR_MAP_INTERLEAVE_NONE,sw,pr,CU_TENSOR_MAP_FLOAT_OOB_FILL_NONE);
}

extern "C" void kernel_launch(void* const* d_in, const int* in_sizes, int n_in, void* d_out, int out_size){
  const bf16* q=(const bf16*)d_in[0]; const bf16* k=(const bf16*)d_in[1]; const bf16* v=(const bf16*)d_in[2];
  const bf16* sh=(const bf16*)d_in[3]; const bf16* K=(const bf16*)d_in[4]; const bf16* Dv=(const bf16*)d_in[5];
  const bf16* wgt=(const bf16*)d_in[7]; const bf16* wup=(const bf16*)d_in[8]; const bf16* wdn=(const bf16*)d_in[9];
  void* fn=nullptr; cudaDriverEntryPointQueryResult qr; cudaGetDriverEntryPoint("cuTensorMapEncodeTiled",&fn,cudaEnableDefault,&qr);
  PFN_encodeTiled enc=(PFN_encodeTiled)fn;
  void* hT; cudaGetSymbolAddress(&hT,g_hT);
  Maps maps;
  make3d(enc,&maps.k,k,512,256,8,8192,1024,8,17,8,CU_TENSOR_MAP_SWIZZLE_NONE,CU_TENSOR_MAP_L2_PROMOTION_L2_128B);
  make3d(enc,&maps.v,v,512,256,8,8192,1024,8,16,8,CU_TENSOR_MAP_SWIZZLE_NONE,CU_TENSOR_MAP_L2_PROMOTION_L2_128B);
  { maps.upfirst = wup<wgt; const bf16* w0 = wup<wgt? wup:wgt; const uint64_t dm = (uint64_t)((wup<wgt? wgt-wup : wup-wgt)*2);
    cuuint64_t gd[4]={F_,D_,2,2}; cuuint64_t gs[3]={F_*2,dm,128}; cuuint32_t bx[4]={64,32,2,2}; cuuint32_t es[4]={1,1,1,1};
    enc(&maps.w64,CU_TENSOR_MAP_DATA_TYPE_BFLOAT16,4,(void*)w0,gd,gs,bx,es,CU_TENSOR_MAP_INTERLEAVE_NONE,CU_TENSOR_MAP_SWIZZLE_128B,CU_TENSOR_MAP_L2_PROMOTION_L2_128B,CU_TENSOR_MAP_FLOAT_OOB_FILL_NONE);
    make3d(enc,&maps.w48,w0,F_,D_,2,F_*2,dm,48,32,2,CU_TENSOR_MAP_SWIZZLE_128B,CU_TENSOR_MAP_L2_PROMOTION_L2_128B); }
  make2d(enc,&maps.wd,wdn,D_,F_,64,176);
  make2d(enc,&maps.ht,hT,S_,D_,64,32);
  { cuuint64_t gd[4]={512,8,16,16}; cuuint64_t gs[3]={1024,8192,131072}; cuuint32_t bx[4]={64,2,4,2}; cuuint32_t es[4]={1,1,1,1};
    enc(&maps.out,CU_TENSOR_MAP_DATA_TYPE_BFLOAT16,4,d_out,gd,gs,bx,es,CU_TENSOR_MAP_INTERLEAVE_NONE,CU_TENSOR_MAP_SWIZZLE_128B,CU_TENSOR_MAP_L2_PROMOTION_NONE,CU_TENSOR_MAP_FLOAT_OOB_FILL_NONE); }
  void* xa; cudaGetSymbolAddress(&xa,g_xa);
  make2d(enc,&maps.xa,xa,8192,128,64,128);
  cudaFuncSetAttribute(fused_kernel,cudaFuncAttributeMaxDynamicSharedMemorySize,SMEM_BYTES);
  fused_kernel<<<128,384,SMEM_BYTES>>>(maps,q,sh,K,Dv,wgt,wup,wdn,(bf16*)d_out);
}
```

```cpp
#include <cuda_runtime.h>
#include <cuda_bf16.h>
#include <cuda.h>
#include <stdint.h>

template<int TA,int TB> __device__ __forceinline__ void wgmma_ss_n176(float* d, uint64_t da, uint64_t db, int sd){
  asm volatile("{ .reg .pred p; setp.ne.b32 p, %90, 0; wgmma.mma_async.sync.aligned.m64n176k16.f32.bf16.bf16 {%0,%1,%2,%3,%4,%5,%6,%7,%8,%9,%10,%11,%12,%13,%14,%15,%16,%17,%18,%19,%20,%21,%22,%23,%24,%25,%26,%27,%28,%29,%30,%31,%32,%33,%34,%35,%36,%37,%38,%39,%40,%41,%42,%43,%44,%45,%46,%47,%48,%49,%50,%51,%52,%53,%54,%55,%56,%57,%58,%59,%60,%61,%62,%63,%64,%65,%66,%67,%68,%69,%70,%71,%72,%73,%74,%75,%76,%77,%78,%79,%80,%81,%82,%83,%84,%85,%86,%87}, %88, %89, p, 1, 1, %91, %92; }"
   : "+f"(d[0]),"+f"(d[1]),"+f"(d[2]),"+f"(d[3]),"+f"(d[4]),"+f"(d[5]),"+f"(d[6]),"+f"(d[7]),"+f"(d[8]),"+f"(d[9]),"+f"(d[10]),"+f"(d[11]),"+f"(d[12]),"+f"(d[13]),"+f"(d[14]),"+f"(d[15]),"+f"(d[16]),"+f"(d[17]),"+f"(d[18]),"+f"(d[19]),"+f"(d[20]),"+f"(d[21]),"+f"(d[22]),"+f"(d[23]),"+f"(d[24]),"+f"(d[25]),"+f"(d[26]),"+f"(d[27]),"+f"(d[28]),"+f"(d[29]),"+f"(d[30]),"+f"(d[31]),"+f"(d[32]),"+f"(d[33]),"+f"(d[34]),"+f"(d[35]),"+f"(d[36]),"+f"(d[37]),"+f"(d[38]),"+f"(d[39]),"+f"(d[40]),"+f"(d[41]),"+f"(d[42]),"+f"(d[43]),"+f"(d[44]),"+f"(d[45]),"+f"(d[46]),"+f"(d[47]),"+f"(d[48]),"+f"(d[49]),"+f"(d[50]),"+f"(d[51]),"+f"(d[52]),"+f"(d[53]),"+f"(d[54]),"+f"(d[55]),"+f"(d[56]),"+f"(d[57]),"+f"(d[58]),"+f"(d[59]),"+f"(d[60]),"+f"(d[61]),"+f"(d[62]),"+f"(d[63]),"+f"(d[64]),"+f"(d[65]),"+f"(d[66]),"+f"(d[67]),"+f"(d[68]),"+f"(d[69]),"+f"(d[70]),"+f"(d[71]),"+f"(d[72]),"+f"(d[73]),"+f"(d[74]),"+f"(d[75]),"+f"(d[76]),"+f"(d[77]),"+f"(d[78]),"+f"(d[79]),"+f"(d[80]),"+f"(d[81]),"+f"(d[82]),"+f"(d[83]),"+f"(d[84]),"+f"(d[85]),"+f"(d[86]),"+f"(d[87]) : "l"(da), "l"(db), "r"(sd), "n"(TA), "n"(TB));
}
template<int TB> __device__ __forceinline__ void wgmma_rs_n8(float* d, uint32_t a0, uint32_t a1, uint32_t a2, uint32_t a3, uint64_t db, int sd){
  asm volatile("{ .reg .pred p; setp.ne.b32 p, %9, 0; wgmma.mma_async.sync.aligned.m64n8k16.f32.bf16.bf16 {%0,%1,%2,%3}, {%4,%5,%6,%7}, %8, p, 1, 1, %10; }"
   : "+f"(d[0]),"+f"(d[1]),"+f"(d[2]),"+f"(d[3]) : "r"(a0),"r"(a1),"r"(a2),"r"(a3), "l"(db), "r"(sd), "n"(TB));
}
template<int TB> __device__ __forceinline__ void wgmma_rs_n16(float* d, uint32_t a0, uint32_t a1, uint32_t a2, uint32_t a3, uint64_t db, int sd){
  asm volatile("{ .reg .pred p; setp.ne.b32 p, %13, 0; wgmma.mma_async.sync.aligned.m64n16k16.f32.bf16.bf16 {%0,%1,%2,%3,%4,%5,%6,%7}, {%8,%9,%10,%11}, %12, p, 1, 1, %14; }"
   : "+f"(d[0]),"+f"(d[1]),"+f"(d[2]),"+f"(d[3]),"+f"(d[4]),"+f"(d[5]),"+f"(d[6]),"+f"(d[7]) : "r"(a0),"r"(a1),"r"(a2),"r"(a3), "l"(db), "r"(sd), "n"(TB));
}
template<int TB> __device__ __forceinline__ void wgmma_rs_n24(float* d, uint32_t a0, uint32_t a1, uint32_t a2, uint32_t a3, uint64_t db, int sd){
  asm volatile("{ .reg .pred p; setp.ne.b32 p, %17, 0; wgmma.mma_async.sync.aligned.m64n24k16.f32.bf16.bf16 {%0,%1,%2,%3,%4,%5,%6,%7,%8,%9,%10,%11}, {%12,%13,%14,%15}, %16, p, 1, 1, %18; }"
   : "+f"(d[0]),"+f"(d[1]),"+f"(d[2]),"+f"(d[3]),"+f"(d[4]),"+f"(d[5]),"+f"(d[6]),"+f"(d[7]),"+f"(d[8]),"+f"(d[9]),"+f"(d[10]),"+f"(d[11]) : "r"(a0),"r"(a1),"r"(a2),"r"(a3), "l"(db), "r"(sd), "n"(TB));
}
template<int TB> __device__ __forceinline__ void wgmma_rs_n32(float* d, uint32_t a0, uint32_t a1, uint32_t a2, uint32_t a3, uint64_t db, int sd){
  asm volatile("{ .reg .pred p; setp.ne.b32 p, %21, 0; wgmma.mma_async.sync.aligned.m64n32k16.f32.bf16.bf16 {%0,%1,%2,%3,%4,%5,%6,%7,%8,%9,%10,%11,%12,%13,%14,%15}, {%16,%17,%18,%19}, %20, p, 1, 1, %22; }"
   : "+f"(d[0]),"+f"(d[1]),"+f"(d[2]),"+f"(d[3]),"+f"(d[4]),"+f"(d[5]),"+f"(d[6]),"+f"(d[7]),"+f"(d[8]),"+f"(d[9]),"+f"(d[10]),"+f"(d[11]),"+f"(d[12]),"+f"(d[13]),"+f"(d[14]),"+f"(d[15]) : "r"(a0),"r"(a1),"r"(a2),"r"(a3), "l"(db), "r"(sd), "n"(TB));
}
template<int TB> __device__ __forceinline__ void wgmma_rs_n40(float* d, uint32_t a0, uint32_t a1, uint32_t a2, uint32_t a3, uint64_t db, int sd){
  asm volatile("{ .reg .pred p; setp.ne.b32 p, %25, 0; wgmma.mma_async.sync.aligned.m64n40k16.f32.bf16.bf16 {%0,%1,%2,%3,%4,%5,%6,%7,%8,%9,%10,%11,%12,%13,%14,%15,%16,%17,%18,%19}, {%20,%21,%22,%23}, %24, p, 1, 1, %26; }"
   : "+f"(d[0]),"+f"(d[1]),"+f"(d[2]),"+f"(d[3]),"+f"(d[4]),"+f"(d[5]),"+f"(d[6]),"+f"(d[7]),"+f"(d[8]),"+f"(d[9]),"+f"(d[10]),"+f"(d[11]),"+f"(d[12]),"+f"(d[13]),"+f"(d[14]),"+f"(d[15]),"+f"(d[16]),"+f"(d[17]),"+f"(d[18]),"+f"(d[19]) : "r"(a0),"r"(a1),"r"(a2),"r"(a3), "l"(db), "r"(sd), "n"(TB));
}
template<int TB> __device__ __forceinline__ void wgmma_rs_n48(float* d, uint32_t a0, uint32_t a1, uint32_t a2, uint32_t a3, uint64_t db, int sd){
  asm volatile("{ .reg .pred p; setp.ne.b32 p, %29, 0; wgmma.mma_async.sync.aligned.m64n48k16.f32.bf16.bf16 {%0,%1,%2,%3,%4,%5,%6,%7,%8,%9,%10,%11,%12,%13,%14,%15,%16,%17,%18,%19,%20,%21,%22,%23}, {%24,%25,%26,%27}, %28, p, 1, 1, %30; }"
   : "+f"(d[0]),"+f"(d[1]),"+f"(d[2]),"+f"(d[3]),"+f"(d[4]),"+f"(d[5]),"+f"(d[6]),"+f"(d[7]),"+f"(d[8]),"+f"(d[9]),"+f"(d[10]),"+f"(d[11]),"+f"(d[12]),"+f"(d[13]),"+f"(d[14]),"+f"(d[15]),"+f"(d[16]),"+f"(d[17]),"+f"(d[18]),"+f"(d[19]),"+f"(d[20]),"+f"(d[21]),"+f"(d[22]),"+f"(d[23]) : "r"(a0),"r"(a1),"r"(a2),"r"(a3), "l"(db), "r"(sd), "n"(TB));
}
template<int TB> __device__ __forceinline__ void wgmma_rs_n56(float* d, uint32_t a0, uint32_t a1, uint32_t a2, uint32_t a3, uint64_t db, int sd){
  asm volatile("{ .reg .pred p; setp.ne.b32 p, %33, 0; wgmma.mma_async.sync.aligned.m64n56k16.f32.bf16.bf16 {%0,%1,%2,%3,%4,%5,%6,%7,%8,%9,%10,%11,%12,%13,%14,%15,%16,%17,%18,%19,%20,%21,%22,%23,%24,%25,%26,%27}, {%28,%29,%30,%31}, %32, p, 1, 1, %34; }"
   : "+f"(d[0]),"+f"(d[1]),"+f"(d[2]),"+f"(d[3]),"+f"(d[4]),"+f"(d[5]),"+f"(d[6]),"+f"(d[7]),"+f"(d[8]),"+f"(d[9]),"+f"(d[10]),"+f"(d[11]),"+f"(d[12]),"+f"(d[13]),"+f"(d[14]),"+f"(d[15]),"+f"(d[16]),"+f"(d[17]),"+f"(d[18]),"+f"(d[19]),"+f"(d[20]),"+f"(d[21]),"+f"(d[22]),"+f"(d[23]),"+f"(d[24]),"+f"(d[25]),"+f"(d[26]),"+f"(d[27]) : "r"(a0),"r"(a1),"r"(a2),"r"(a3), "l"(db), "r"(sd), "n"(TB));
}
template<int TB> __device__ __forceinline__ void wgmma_rs_n64(float* d, uint32_t a0, uint32_t a1, uint32_t a2, uint32_t a3, uint64_t db, int sd){
  asm volatile("{ .reg .pred p; setp.ne.b32 p, %37, 0; wgmma.mma_async.sync.aligned.m64n64k16.f32.bf16.bf16 {%0,%1,%2,%3,%4,%5,%6,%7,%8,%9,%10,%11,%12,%13,%14,%15,%16,%17,%18,%19,%20,%21,%22,%23,%24,%25,%26,%27,%28,%29,%30,%31}, {%32,%33,%34,%35}, %36, p, 1, 1, %38; }"
   : "+f"(d[0]),"+f"(d[1]),"+f"(d[2]),"+f"(d[3]),"+f"(d[4]),"+f"(d[5]),"+f"(d[6]),"+f"(d[7]),"+f"(d[8]),"+f"(d[9]),"+f"(d[10]),"+f"(d[11]),"+f"(d[12]),"+f"(d[13]),"+f"(d[14]),"+f"(d[15]),"+f"(d[16]),"+f"(d[17]),"+f"(d[18]),"+f"(d[19]),"+f"(d[20]),"+f"(d[21]),"+f"(d[22]),"+f"(d[23]),"+f"(d[24]),"+f"(d[25]),"+f"(d[26]),"+f"(d[27]),"+f"(d[28]),"+f"(d[29]),"+f"(d[30]),"+f"(d[31]) : "r"(a0),"r"(a1),"r"(a2),"r"(a3), "l"(db), "r"(sd), "n"(TB));
}
template<int N,int TA,int TB> __device__ __forceinline__ void wgmma_ss(float* d, uint64_t da, uint64_t db, int sd){
  if constexpr(N==176) wgmma_ss_n176<TA,TB>(d,da,db,sd);
}
template<int N,int TB> __device__ __forceinline__ void wgmma_rs(float* d, uint32_t a0,uint32_t a1,uint32_t a2,uint32_t a3, uint64_t db, int sd){
  if constexpr(N==8) wgmma_rs_n8<TB>(d,a0,a1,a2,a3,db,sd);
  if constexpr(N==16) wgmma_rs_n16<TB>(d,a0,a1,a2,a3,db,sd);
  if constexpr(N==24) wgmma_rs_n24<TB>(d,a0,a1,a2,a3,db,sd);
  if constexpr(N==32) wgmma_rs_n32<TB>(d,a0,a1,a2,a3,db,sd);
  if constexpr(N==40) wgmma_rs_n40<TB>(d,a0,a1,a2,a3,db,sd);
  if constexpr(N==48) wgmma_rs_n48<TB>(d,a0,a1,a2,a3,db,sd);
  if constexpr(N==56) wgmma_rs_n56<TB>(d,a0,a1,a2,a3,db,sd);
  if constexpr(N==64) wgmma_rs_n64<TB>(d,a0,a1,a2,a3,db,sd);
}

typedef __nv_bfloat16 bf16;
constexpr int S_ = 2048, D_ = 512, F_ = 1376, FS = 176;

__device__ __forceinline__ uint32_t smem_u32(const void* p){ return (uint32_t)__cvta_generic_to_shared(p); }
__device__ __forceinline__ void mbar_init(uint32_t bar, uint32_t cnt){ asm volatile("mbarrier.init.shared::cta.b64 [%0], %1;"::"r"(bar),"r"(cnt):"memory"); }
__device__ __forceinline__ void mbar_expect_tx(uint32_t bar, uint32_t bytes){ asm volatile("mbarrier.arrive.expect_tx.shared::cta.b64 _, [%0], %1;"::"r"(bar),"r"(bytes):"memory"); }
__device__ __forceinline__ void mbar_arrive(uint32_t bar){ asm volatile("mbarrier.arrive.shared::cta.b64 _, [%0];"::"r"(bar):"memory"); }
__device__ __forceinline__ void mbar_arrive_n(uint32_t bar, uint32_t n){ asm volatile("mbarrier.arrive.shared::cta.b64 _, [%0], %1;"::"r"(bar),"r"(n):"memory"); }
__device__ __forceinline__ void mbar_arrive_cl(uint32_t cbar){ asm volatile("mbarrier.arrive.shared::cluster.b64 _, [%0];"::"r"(cbar):"memory"); }
__device__ __forceinline__ uint32_t mapa(uint32_t a, uint32_t cta){ uint32_t r; asm volatile("mapa.shared::cluster.u32 %0, %1, %2;":"=r"(r):"r"(a),"r"(cta)); return r; }
__device__ __forceinline__ void mbar_wait(uint32_t bar, uint32_t ph){
  asm volatile("{ .reg .pred p; .reg .u32 c; mov.u32 c, 0;\n"
               "WL: mbarrier.try_wait.parity.shared::cta.b64 p, [%0], %1; @p bra WD; add.u32 c,c,1; setp.lt.u32 p, c, 1000000; @p bra WL; trap;\n"
               "WD: }"::"r"(bar),"r"(ph):"memory"); }
__device__ __forceinline__ uint32_t mbar_test(uint32_t bar, uint32_t ph){ uint32_t ok; asm volatile("{ .reg .pred p; mbarrier.test_wait.parity.shared::cta.b64 p, [%1], %2; selp.u32 %0,1,0,p; }":"=r"(ok):"r"(bar),"r"(ph):"memory"); return ok; }
__device__ __forceinline__ void spin_guard(int n){ asm volatile("{ .reg .pred p; setp.gt.s32 p, %0, 2000000; @p trap; }"::"r"(n)); }
__device__ __forceinline__ bool elect_one(){ uint32_t p; asm volatile("{ .reg .pred P; elect.sync _|P, 0xffffffff; selp.u32 %0,1,0,P; }":"=r"(p)); return p; }
__device__ __forceinline__ void tma2d(uint32_t dst, const CUtensorMap* m, int c0, int c1, uint32_t bar){
  asm volatile("cp.async.bulk.tensor.2d.shared::cluster.global.mbarrier::complete_tx::bytes [%0], [%1, {%3, %4}], [%2];"::"r"(dst),"l"(m),"r"(bar),"r"(c0),"r"(c1):"memory"); }
__device__ __forceinline__ void tma2d_mc(uint32_t dst, const CUtensorMap* m, int c0, int c1, uint32_t bar){
  asm volatile("cp.async.bulk.tensor.2d.shared::cluster.global.mbarrier::complete_tx::bytes.multicast::cluster [%0], [%1, {%3, %4}], [%2], %5;"::"r"(dst),"l"(m),"r"(bar),"r"(c0),"r"(c1),"h"((uint16_t)3):"memory"); }
__device__ __forceinline__ void wg_fence(){ asm volatile("wgmma.fence.sync.aligned;":::"memory"); }
__device__ __forceinline__ void wg_commit(){ asm volatile("wgmma.commit_group.sync.aligned;":::"memory"); }
template<int N> __device__ __forceinline__ void wg_wait(){ asm volatile("wgmma.wait_group.sync.aligned %0;"::"n"(N):"memory"); }
__device__ __forceinline__ uint64_t make_desc(uint32_t addr, uint32_t lbo, uint32_t sbo, uint32_t sw){ return (uint64_t)((addr&0x3FFFF)>>4) | ((uint64_t)((lbo&0x3FFFF)>>4)<<16) | ((uint64_t)((sbo&0x3FFFF)>>4)<<32) | ((uint64_t)sw<<62); }
__device__ __forceinline__ void ldsm4t(uint32_t a, uint32_t& r0, uint32_t& r1, uint32_t& r2, uint32_t& r3){ asm volatile("ldmatrix.sync.aligned.m8n8.x4.trans.shared.b16 {%0,%1,%2,%3}, [%4];":"=r"(r0),"=r"(r1),"=r"(r2),"=r"(r3):"r"(a):"memory"); }
__device__ __forceinline__ uint32_t pack_bf16(float lo, float hi){ uint32_t r; asm("cvt.rn.bf16x2.f32 %0, %1, %2;":"=r"(r):"f"(hi),"f"(lo)); return r; }
__device__ __forceinline__ float bf_lo(uint32_t v){ return __uint_as_float(v<<16); }
__device__ __forceinline__ float bf_hi(uint32_t v){ return __uint_as_float(v&0xffff0000u); }
__device__ __forceinline__ float rbf(float x){ return __bfloat162float(__float2bfloat16(x)); }
__device__ __forceinline__ uint32_t hadd2_bf16(uint32_t a, uint32_t b){ uint32_t r; asm("add.rn.bf16x2 %0, %1, %2;":"=r"(r):"r"(a),"r"(b)); return r; }
__device__ __forceinline__ float tanh_fast(float x){ float r; asm("tanh.approx.f32 %0, %1;":"=f"(r):"f"(x)); return r; }

__device__ __forceinline__ void st_rlx128(void* p, uint32_t a, uint32_t b, uint32_t c, uint32_t d){
  asm volatile("{ .reg .b64 l,h; .reg .b128 v; mov.b64 l,{%1,%2}; mov.b64 h,{%3,%4}; mov.b128 v,{l,h}; st.relaxed.gpu.global.b128 [%0], v; }"::"l"(p),"r"(a),"r"(b),"r"(c),"r"(d):"memory"); }
__device__ __forceinline__ void ld_rlx128(const void* p, uint4& v){
  asm volatile("{ .reg .b64 l,h; .reg .b128 v; ld.relaxed.gpu.global.b128 v, [%4]; mov.b128 {l,h}, v; mov.b64 {%0,%1}, l; mov.b64 {%2,%3}, h; }":"=r"(v.x),"=r"(v.y),"=r"(v.z),"=r"(v.w):"l"(p):"memory"); }
__device__ __forceinline__ void st_async128(uint32_t dst, uint32_t a, uint32_t b, uint32_t c, uint32_t d, uint32_t cbar){
  asm volatile("st.async.weak.shared::cluster.mbarrier::complete_tx::bytes.v4.b32 [%0], {%1,%2,%3,%4}, [%5];"::"r"(dst),"r"(a),"r"(b),"r"(c),"r"(d),"r"(cbar)); }
__device__ __forceinline__ void bulk_g2s(uint32_t dst, const void* src, uint32_t bytes, uint32_t bar){
  asm volatile("cp.async.bulk.shared::cluster.global.mbarrier::complete_tx::bytes [%0], [%1], %2, [%3];"::"r"(dst),"l"(src),"r"(bytes),"r"(bar):"memory"); }
__device__ __forceinline__ void lds128(uint32_t a, uint32_t& x, uint32_t& y, uint32_t& z, uint32_t& w){ asm volatile("ld.shared.v4.u32 {%0,%1,%2,%3}, [%4];":"=r"(x),"=r"(y),"=r"(z),"=r"(w):"r"(a):"memory"); }
__device__ __forceinline__ void tma4d_red_add(const CUtensorMap* m, int c0, int c1, int c2, int c3, uint32_t src){
  asm volatile("cp.reduce.async.bulk.tensor.4d.global.shared::cta.add.tile.bulk_group [%0, {%1, %2, %3, %4}], [%5];"::"l"(m),"r"(c0),"r"(c1),"r"(c2),"r"(c3),"r"(src):"memory"); }
__device__ __forceinline__ void stsm4_nm(uint32_t a, uint32_t r0, uint32_t r1, uint32_t r2, uint32_t r3){ asm volatile("stmatrix.sync.aligned.m8n8.x4.shared.b16 [%0], {%1,%2,%3,%4};"::"r"(a),"r"(r0),"r"(r1),"r"(r2),"r"(r3)); }
__device__ __forceinline__ void tma3d(uint32_t dst, const CUtensorMap* m, int c0, int c1, int c2, uint32_t bar){
  asm volatile("cp.async.bulk.tensor.3d.shared::cluster.global.mbarrier::complete_tx::bytes [%0], [%1, {%3, %4, %5}], [%2];"::"r"(dst),"l"(m),"r"(bar),"r"(c0),"r"(c1),"r"(c2):"memory"); }
__device__ __forceinline__ uint32_t lds32(uint32_t a){ uint32_t v; asm volatile("ld.shared.u32 %0, [%1];":"=r"(v):"r"(a)); return v; }
__device__ __forceinline__ void sts128(uint32_t a, uint32_t x, uint32_t y, uint32_t z, uint32_t w){ asm volatile("st.shared.v4.u32 [%0], {%1,%2,%3,%4};"::"r"(a),"r"(x),"r"(y),"r"(z),"r"(w):"memory"); }
__device__ __forceinline__ uint4 ldg_nc128(const void* p){ uint4 v; asm volatile("ld.global.nc.L1::no_allocate.v4.u32 {%0,%1,%2,%3}, [%4];":"=r"(v.x),"=r"(v.y),"=r"(v.z),"=r"(v.w):"l"(p)); return v; }
__device__ __forceinline__ uint32_t hmul2_bf16(uint32_t a, uint32_t b){ uint32_t r; asm("mul.rn.bf16x2 %0, %1, %2;":"=r"(r):"r"(a),"r"(b)); return r; }
__device__ __forceinline__ uint32_t hfma2_bf16(uint32_t a, uint32_t b, uint32_t c){ uint32_t r; asm("fma.rn.bf16x2 %0, %1, %2, %3;":"=r"(r):"r"(a),"r"(b),"r"(c)); return r; }
__device__ __forceinline__ uint32_t hsub2_bf16(uint32_t a, uint32_t b){ uint32_t r; asm("sub.rn.bf16x2 %0, %1, %2;":"=r"(r):"r"(a),"r"(b)); return r; }
__device__ __forceinline__ void signal_add(unsigned* p){ asm volatile("fence.acq_rel.gpu;":::"memory"); asm volatile("red.relaxed.gpu.global.add.u32 [%0], 1;"::"l"(p):"memory"); }
__device__ __forceinline__ void lds128_nm(uint32_t a, uint32_t& x, uint32_t& y, uint32_t& z, uint32_t& w){ asm volatile("ld.shared.v4.u32 {%0,%1,%2,%3}, [%4];":"=r"(x),"=r"(y),"=r"(z),"=r"(w):"r"(a)); }
__device__ __forceinline__ float ln_rstd(float var){
  float sq, r; asm("sqrt.approx.f32 %0, %1;":"=f"(sq):"f"(rbf(rbf(var)+1e-5f))); asm("rcp.approx.f32 %0, %1;":"=f"(r):"f"(rbf(sq))); return r; }
__device__ __forceinline__ float4 gather_sum(const uint4* src, int n, int stride, uint32_t par){
  float4 c=make_float4(0.f,0.f,0.f,0.f);
  #pragma unroll 1
  for(int kb=0;kb<n;kb+=4){
    uint4 v[4]; int it=0;
    do{
      #pragma unroll
      for(int u=0;u<4;u++) ld_rlx128(src+u*stride, v[u]);
      spin_guard(++it);
    }while(((v[0].x^par)|(v[1].x^par)|(v[2].x^par)|(v[3].x^par))&1);
    #pragma unroll
    for(int u=0;u<4;u++){ c.x+=__uint_as_float(v[u].x); c.y+=__uint_as_float(v[u].y); c.z+=__uint_as_float(v[u].z); c.w+=__uint_as_float(v[u].w); }
    src+=4*stride;
  }
  return c;
}
__host__ __device__ __forceinline__ int pos2row(int pos){
  const int P = 1 - (pos >> 10), thr = (pos & 1023) >> 3, k = (pos>>2)&1, h = (pos>>1)&1, e = pos&1;
  const int w = thr >> 5, tp = (thr >> 3)&3, j = (thr >> 1)&3, p = thr & 1;
  return 16*(127 - (64*P + 16*j + 8*k + 2*tp + e)) + 8*h + 2*w + p;
}

__device__ __align__(1024) bf16 g_hT[D_*S_];
__device__ __align__(1024) uint4 g_xa[128*128*8];
__device__ __align__(1024) uint4 g_qs[128*8];
__device__ uint4 g_stat[16*2*8*32];
__device__ uint4 g_csp[8*16*88];
__device__ uint4 g_cs2[8*96];
__device__ unsigned g_cnt[4*32];
#define STAMP(i)

#define QDELAY 1700
#define KV0 3
#define XAFTER 4
#define XPOS 3
#define ZKV 3
#define WSTART 5
#define W9 2
#define PACE 2
#define CSLEEP 600
#define SKW 2
#define STX0 2
#define STX1 1
#define CSUN 4
#define NIN 7
constexpr int CSU = CSUN;
constexpr uint32_t G2_CH = 0x33221010u, G2_PEER = 0xAC;
constexpr int NS = 6, WSLOT = 24576, NX = 4, XSLOT = 8192;
constexpr int OFF_RES0 = 0, OFF_X = 8192, OFF_RES1 = 73728, OFF_W = 81920;
constexpr int OFF_CS = OFF_W + NS*WSLOT, OFF_ROW = OFF_CS + 2*FS*4, OFF_BAR = OFF_ROW + 1024;
constexpr int TBL = 8320, UPL = 2112, UCH = 2*UPL, QP = 1088, KVCH = 4224;
constexpr int OFF_TBL = 32768, OFF_U = OFF_TBL + 4*TBL, OFF_XAL = 83968, OFF_XAE = OFF_W + 2*WSLOT;
constexpr int OFF_IMG = 0, OFF_X8 = OFF_XAL + 16384, OFF_ZB = OFF_X8 + 4096;
#define KVOFF(T) (OFF_W + 3*WSLOT + (T)*KVCH - ((T)>>2)*(2*WSLOT+4*KVCH))
constexpr int OFF_KV = OFF_W + 3*WSLOT, OFF_Q = OFF_W + 4*WSLOT, OFF_SK = OFF_Q + 16*QP;
static_assert(OFF_U + 4*UCH <= OFF_XAL && OFF_XAL + 16384 <= OFF_W + WSLOT, "overlay");
constexpr int B_WFULL = 0, B_WEMPTY = B_WFULL+NS, B_XFULL = B_WEMPTY+NS, B_XEMPTY = B_XFULL+2*NX, B_PRDY = B_XEMPTY+2*NX, B_AFULL = B_PRDY+2,
              B_ONE = B_AFULL+2, B_FB = B_ONE, B_INIT = B_FB+2, B_XA = B_INIT+2, B_PAR = B_XA+2, B_TD = B_PAR+2, B_KV = B_TD+1, B_U = B_KV+8, B_HD = B_U+8, B_SK = B_HD+2, B_Q = B_SK+1, B_QD = B_Q+8, B_SC = B_QD+1, B_X03 = B_SC+1, B_RT = B_X03+1, NBAR = B_RT+2;
constexpr int OFF_MISC = (OFF_BAR + NBAR*8 + 15)&~15;
constexpr int SMEM_BYTES = OFF_MISC + 16;
static_assert(SMEM_BYTES<=232448,"smem");

struct Maps { CUtensorMap k, v, xa, w64, w48, wd, ht, out; int upfirst; };

__device__ __forceinline__ void load_w_stage(const Maps& maps, uint32_t dst, int col, int k0, uint32_t fb){
  asm volatile("cp.async.bulk.tensor.4d.shared::cluster.global.mbarrier::complete_tx::bytes [%0], [%1, {%3, %4, %5, %5}], [%2];"::"r"(dst),"l"(&maps.w64),"r"(fb),"r"(col),"r"(k0),"r"(0):"memory");
  tma3d(dst+16384, &maps.w48, col+128, k0, 0, fb);
}

template<int N> __device__ __forceinline__ void conv_mma(float* acc, const uint32_t* R, uint64_t db){
  wgmma_rs<N,0>(acc, R[0],R[1],R[2],R[3], db,   1);
  wgmma_rs<N,0>(acc, R[4],R[5],R[6],R[7], db+1, 1);
}
__device__ __forceinline__ void conv_lda(uint32_t* R, const uint32_t* tb, int off){
  R[0]=lds32(tb[0]+off); R[1]=lds32(tb[1]+off); R[3]=lds32(tb[2]+off); R[5]=lds32(tb[3]+off); R[7]=lds32(tb[4]+off);
}
__device__ __forceinline__ void conv_dup(uint32_t* R){
  asm volatile("mov.b32 %0, %1;":"=r"(R[2]):"r"(R[1])); asm volatile("mov.b32 %0, %1;":"=r"(R[4]):"r"(R[3])); asm volatile("mov.b32 %0, %1;":"=r"(R[6]):"r"(R[5]));
}
__device__ __forceinline__ void zero4(float* a){
  #pragma unroll
  for(int i=0;i<4;i++) asm volatile("mov.b32 %0, 0;":"=f"(a[i]));
}
__device__ __forceinline__ uint32_t tid_now(){ uint32_t t; asm volatile("mov.u32 %0, %%tid.x;":"=r"(t)); return t; }
__device__ __forceinline__ void load_xs(uint4* x, uint4* st, uint32_t sb, int warp, int lane){
  const uint32_t tw = (warp&3)*32+lane, pc = ((warp>>2)*2)^(tw&7);
  #pragma unroll
  for(int i=0;i<4;i++) lds128(sb+OFF_XAL+tw*128+((pc^(i&1)^((i>>1)*4))<<4), x[i].x,x[i].y,x[i].z,x[i].w);
  #pragma unroll
  for(int i=0;i<8;i++) lds128(sb+OFF_XAE+tw*128+((i^(tw&7))<<4), st[i].x,st[i].y,st[i].z,st[i].w);
}
__device__ __forceinline__ void check_xs(uint4* x, uint4* st, uint32_t ep, uint32_t sb, int warp){
  for(int n=0;n<2000000;n++){
    uint32_t bad=0;
    #pragma unroll
    for(int i=0;i<8;i++) bad|=st[i].w^ep;
    if(!bad && x[0].x && x[1].x && x[2].x && x[3].x) break;
    const uint32_t t2=tid_now()&127, pc = ((warp>>2)*2)^(t2&7);
    #pragma unroll
    for(int i=0;i<4;i++) ld_rlx128(&g_xa[blockIdx.x*1024+t2*8+(pc^(i&1)^((i>>1)*4))], x[i]);
    #pragma unroll
    for(int i=0;i<8;i++) ld_rlx128(&g_qs[t2*8+(i^(t2&7))], st[i]);
  }
  __syncwarp();
}
__device__ __forceinline__ void ln_x(uint4* x, const uint4* st, uint4* a){
#define LNA(X,S) ({ const uint32_t d_=hsub2_bf16(X,S.x); hfma2_bf16(d_,S.y,hmul2_bf16(d_,S.z)); })
  #pragma unroll
  for(int i=0;i<2;i++){
    x[i].x=~x[i].x;
    a[i].x=LNA(x[i].x,st[0]); a[i].y=LNA(x[i].y,st[1]); a[i].z=LNA(x[i].z,st[2]); a[i].w=LNA(x[i].w,st[3]);
  }
}
template<int PART> __device__ __forceinline__ void conv_put(const float* a0, const float* a1, uint32_t sb, int warp, int lane){
  const uint32_t eb = sb + (PART? OFF_IMG+warp*4096 : OFF_TBL+(warp>>2)*2*TBL+(warp&3)*4096), x8 = sb+OFF_X8+warp*512;
  const uint32_t rho = (lane&24)|((lane&3)<<1)|((lane>>2)&1);
  #pragma unroll
  for(int ii=0;ii<8;ii++){
    const uint32_t w0=pack_bf16(a0[4*ii],a0[4*ii+1]), w1=pack_bf16(a0[4*ii+2],a0[4*ii+3]), w2=pack_bf16(a1[4*ii],a1[4*ii+1]), w3=pack_bf16(a1[4*ii+2],a1[4*ii+3]);
    sts128(eb+rho*128+(((rho+ii)&7)<<4), w0,w1,w2,w3);
    if(PART && ii==0) sts128(x8+rho*16, w0,w1,w2,w3);
  }
  __syncwarp();
}
template<int PART> __device__ __forceinline__ void conv_get(const uint4* x, const uint4* a, uint32_t sb, int warp, int lane){
  const int cb = blockIdx.x, chl = (warp>>2)*2;
  const uint32_t tw = (warp&3)*32+lane;
  const uint32_t eb = sb + (PART? OFF_IMG+warp*4096 : OFF_TBL+(warp>>2)*2*TBL+(warp&3)*4096), x8 = sb+OFF_X8+warp*512;
  uint4 d[4][2];
  #pragma unroll
  for(int c=0;c<4;c++){
    const uint32_t tc = (lane>>3)+c, rho = c*8+((tc&3)<<1)+(lane&1), sl = (lane&6)+(tc>>2);
    lds128(eb+rho*128+(((rho+sl)&7)<<4), d[c][0].x,d[c][0].y,d[c][0].z,d[c][0].w);
    uint32_t ad = eb+rho*128+(((rho+sl+1)&7)<<4);
    if(c>0 && sl==7) ad = PART? sb+OFF_U+128*16 : x8+rho*16;
    lds128(ad, d[c][1].x,d[c][1].y,d[c][1].z,d[c][1].w);
  }
#define SUM4(K,F) hadd2_bf16(hadd2_bf16(d[0][K].F,d[1][K].F),hadd2_bf16(d[2][K].F,d[3][K].F))
  uint4 o0, o1;
  o0.x=hadd2_bf16(x[0].x,hmul2_bf16(a[0].x,SUM4(0,x))); o0.y=hadd2_bf16(x[0].y,hmul2_bf16(a[0].y,SUM4(0,y)));
  o0.z=hadd2_bf16(x[0].z,hmul2_bf16(a[0].z,SUM4(1,x))); o0.w=hadd2_bf16(x[0].w,hmul2_bf16(a[0].w,SUM4(1,y)));
  o1.x=hadd2_bf16(x[1].x,hmul2_bf16(a[1].x,SUM4(0,z))); o1.y=hadd2_bf16(x[1].y,hmul2_bf16(a[1].y,SUM4(0,w)));
  o1.z=hadd2_bf16(x[1].z,hmul2_bf16(a[1].z,SUM4(1,z))); o1.w=hadd2_bf16(x[1].w,hmul2_bf16(a[1].w,SUM4(1,w)));
  uint4* dst = (uint4*)(g_hT + (cb*4+chl)*2048 + (1-PART)*1024) + tw;
  const uint32_t par = lds32(sb+OFF_MISC)&1;
  o0.x=(o0.x&~1u)|par; o1.x=(o1.x&~1u)|par;
  dst[0]=o0; dst[256]=o1;
}

__device__ __forceinline__ bool x_bad(uint32_t sb, int wg, int wq, int lane){
  const uint32_t xbase = sb+OFF_X+wg*NX*XSLOT, rbase = sb+(wg? OFF_RES1:OFF_RES0), par = lds32(sb+OFF_MISC), co = lane*128+(((2*wq)^(lane&7))<<4);
  uint32_t bad=0;
  #pragma unroll
  for(int i=0;i<8;i++) bad |= lds32((i<6? xbase+i*4096 : rbase+(i-6)*4096)+co)^par;
  return __any_sync(~0u, bad&1);
}
__device__ __forceinline__ void first_x(const Maps& maps, uint32_t sb, int w){
  const int b = blockIdx.x, rank = b&1, rt = b>>3;
  const uint32_t bar = sb+OFF_BAR, xf = bar+8*(B_XFULL+w*NX), xd = sb+OFF_X+w*NX*XSLOT+rank*4096, rb = sb+(w? OFF_RES1:OFF_RES0);
  const int c0 = w*1024+rt*64, k0 = (rt>>1)+w*(SKW/2), cr = rank*256+((b>>1)&3)*64;
  mbar_expect_tx(xf, 4*XSLOT); mbar_arrive(xf+8); mbar_arrive(xf+16);
  const unsigned tgt = lds32(sb+OFF_MISC)*128;
  mbar_wait(bar+8*(B_HD+w), 0);
  {
    unsigned v; int n=0;
    asm volatile("red.relaxed.gpu.global.add.u32 [%0], 1;"::"l"(&g_cnt[w? 0:96]):"memory");
    do{ asm volatile("ld.relaxed.gpu.global.u32 %0, [%1];":"=r"(v):"l"(&g_cnt[w? 0:96]):"memory"); }while((int)(v-tgt)<0 && ++n<2000000);
  }
  tma2d_mc(xd,         &maps.ht, c0, (k0&7)*64+rank*32,     xf);
  tma2d_mc(xd+XSLOT,   &maps.ht, c0, ((k0+1)&7)*64+rank*32, xf);
  tma2d_mc(xd+2*XSLOT, &maps.ht, c0, ((k0+2)&7)*64+rank*32, xf);
  tma2d(rb,      &maps.ht, c0, cr,    xf);
  tma2d(rb+4096, &maps.ht, c0, cr+32, xf);
}

__global__ void __cluster_dims__(2,1,1) __launch_bounds__(384,1)
fused_kernel(const __grid_constant__ Maps maps, const bf16* __restrict__ q, const bf16* __restrict__ shk, const bf16* __restrict__ ssmk,
             const bf16* __restrict__ ssmD, const bf16* __restrict__ wgt, const bf16* __restrict__ wup, const bf16* __restrict__ wdn, bf16* __restrict__ out){
  extern __shared__ __align__(1024) uint8_t smem_raw[];
  unsigned c_begin; asm volatile("mov.u32 %0, %%clock;":"=r"(c_begin));
  const uint32_t sb = smem_u32(smem_raw);
  const int tid = threadIdx.x, lane = tid&31;
  const int warp = __shfl_sync(0xffffffffu, tid>>5, 0);
  const int wg = warp>>2;
  const int b = blockIdx.x, rank = b&1;
  const int f = b&7, rt = b>>3, fp = f>>1;
  const uint32_t bar = sb+OFF_BAR;

  if(wg==2){
    asm volatile("setmaxnreg.dec.sync.aligned.u32 56;");
    STAMP(58);
    const int cg = b>>1;
    const int cb = cg*2+rank;
    unsigned epoch = 0; uint4 shw = make_uint4(0,0,0,0); uint2 dd = make_uint2(0,0);
    if(warp!=9){
      asm volatile("ld.relaxed.gpu.global.u32 %0, [%1];":"=r"(epoch):"l"(&g_cnt[(lane&3)*32]));
      shw = ldg_nc128(shk + (cg*8+(lane&3)*2)*4);
      asm volatile("ld.global.nc.v2.u32 {%0,%1}, [%2];":"=r"(dd.x),"=r"(dd.y):"l"(ssmD + cb*4));
    }
    auto ldkv=[&](int i){
      const uint32_t fb=bar+8*(B_KV+i);
      mbar_expect_tx(fb, 2176+2048);
      tma3d(sb+KVOFF(i),      &maps.k, cg*8, i*32+rank*16-1, 0, fb);
      tma3d(sb+KVOFF(i)+2176, &maps.v, cg*8, i*32+rank*16,   0, fb);
    };
    if(warp==9){ if(lane<3) asm volatile("prefetch.tensormap [%0];"::"l"(&maps.k+lane):"memory"); }
    STAMP(51+warp);
    asm volatile("bar.sync 0;":::"memory");
    asm volatile("barrier.cluster.arrive.relaxed.aligned;":::"memory");
    if(warp==9){
      { unsigned c1; do{ asm volatile("mov.u32 %0, %%clock;":"=r"(c1)); }while(c1-c_begin<QDELAY); }
      if(elect_one()){
        mbar_expect_tx(bar+8*B_SK, 16384);
        bulk_g2s(sb+OFF_SK, ssmk+cb*4*2048, 16384, bar+8*B_SK);
        #pragma unroll
        for(int i=0;i<KV0;i++) ldkv(i);
      }
      __syncwarp();
      mbar_wait(bar+8*B_QD, 0);
      STAMP(79);
      if(elect_one()){
        asm volatile("cp.async.bulk.tensor.2d.global.shared::cta.bulk_group [%0, {%1, %2}], [%3];"::"l"(&maps.xa),"r"(b*64),"r"(0),"r"(sb+OFF_IMG):"memory");
        asm volatile("cp.async.bulk.commit_group;":::"memory");
        #pragma unroll 1
        for(int i=KV0;i<8;i++){
          ldkv(i);
          if(i==XAFTER){
            asm volatile("cp.async.bulk.wait_group.read 0;":::"memory");
            mbar_wait(bar+8*(B_KV+XPOS), 0);
            mbar_expect_tx(bar+8*B_XA, 32768); bulk_g2s(sb+OFF_XAL, &g_xa[cb*1024], 16384, bar+8*B_XA); bulk_g2s(sb+OFF_XAE, g_qs, 16384, bar+8*B_XA);
            STAMP(66);
          }
        }
        mbar_wait(bar+8*B_WEMPTY, 0);
        mbar_wait(bar+8*(B_KV+ZKV), 0);
        #pragma unroll
        for(int i=0;i<8;i++) asm volatile("cp.async.bulk.global.shared::cta.bulk_group [%0], [%1], 2048;"::"l"(out+b*8192+i*1024),"r"(sb+OFF_ZB):"memory");
        asm volatile("cp.async.bulk.commit_group;":::"memory");
        mbar_wait(bar+8*(B_KV+WSTART), 0);
        #pragma unroll 1
        for(int it=0;it<W9;it++){
          mbar_wait(bar+8*(B_WEMPTY+it), 0);
          if(it>=PACE) mbar_wait(bar+8*(B_WFULL+it-PACE), 0);
          mbar_expect_tx(bar+8*(B_WFULL+it), 22528);
          load_w_stage(maps, sb+OFF_W+(5-it)*WSLOT, f*FS, ((it+(rt&14))&15)*32, bar+8*(B_WFULL+it));
          STAMP(24+it);
        }
        asm volatile("cp.async.bulk.wait_group 0;":::"memory");
        asm volatile("fence.proxy.async.global;":::"memory");
        mbar_arrive(bar+8*(B_HD+1));
        STAMP(30);
      }
      __syncwarp();
    }
    asm volatile("":"+r"(epoch));
    epoch = (epoch>>7)+1;
    if(warp==11){
      if(lane==0) sts128(sb+OFF_MISC, epoch, dd.x, dd.y, 0);
      __syncwarp();
      if(lane==0) mbar_arrive(bar+8*B_SC);
    }
    if(warp==8 && lane<5) asm volatile("prefetch.tensormap [%0];"::"l"(&maps.w64+lane):"memory");
    if(warp==9){ mbar_wait(bar+8*B_SC, 0); epoch = lds32(sb+OFF_MISC); }
    const uint32_t par = epoch&1;
    auto ldx=[&](int w, int it){
      const uint32_t fb = bar+8*(B_XFULL+w*NX+(it&3));
      mbar_expect_tx(fb, XSLOT);
      tma2d_mc(sb+OFF_X+(w*NX+(it&3))*XSLOT+rank*4096, &maps.ht, w*1024+rt*64, ((it+(rt>>1)+w*(SKW/2))&7)*64+rank*32, fb);
    };
    if(warp!=9){
      const int cp = lane&3;
      uint32_t sw[4];
      { const uint4 w = shw;
        sw[0]=__byte_perm(w.x,w.z,0x5410); sw[1]=__byte_perm(w.x,w.z,0x7632); sw[2]=__byte_perm(w.y,w.w,0x5410); sw[3]=__byte_perm(w.y,w.w,0x7632); }
      const uint32_t udst = mapa(sb+OFF_U+(cp&1)*2*UCH, cp>>1), ubar = mapa(bar+8*B_U, cp>>1);
      asm volatile("barrier.cluster.wait.aligned;":::"memory");
      #pragma unroll 1
      for(int tk=(warp==8? 2:warp-10); tk<16; tk+=3){
        const int T=tk>>1, gl=(tk&1)*8+(lane>>2);
        mbar_wait(bar+8*(B_KV+T), 0);
        if(!(tk&1)) STAMP(8+T);
        const uint32_t ka = sb+KVOFF(T)+gl*16+cp*4, va = ka+2176;
        uint32_t kk[11], u[8];
        #pragma unroll
        for(int r=0;r<3;r++) kk[r]=lds32(ka+(5+r)*272);
        #pragma unroll
        for(int r=0;r<8;r++){ kk[3+r]=lds32(ka+16+r*272); u[r]=lds32(va+r*256); }
        #pragma unroll
        for(int r=0;r<8;r++){
          uint32_t a=hmul2_bf16(kk[r],sw[3]); a=hadd2_bf16(a,hmul2_bf16(kk[r+1],sw[2])); a=hadd2_bf16(a,hmul2_bf16(kk[r+2],sw[1])); a=hadd2_bf16(a,hmul2_bf16(kk[r+3],sw[0]));
          u[r]=hmul2_bf16(a,u[r]);
        }
        const int R = 255-(T*32+rank*16+gl);
        const uint32_t d = udst + (R&1)*UPL + (R>>1)*16;
        st_async128(d,     __byte_perm(u[7],u[6],0x5410), __byte_perm(u[5],u[4],0x5410), __byte_perm(u[3],u[2],0x5410), __byte_perm(u[1],u[0],0x5410), ubar+8*T);
        st_async128(d+UCH, __byte_perm(u[7],u[6],0x7632), __byte_perm(u[5],u[4],0x7632), __byte_perm(u[3],u[2],0x7632), __byte_perm(u[1],u[0],0x7632), ubar+8*T);
      }
      __syncwarp();
      if(lane==0) mbar_arrive(bar+8*B_TD);
    } else {
      asm volatile("barrier.cluster.wait.aligned;":::"memory");
    }
    if(warp==8){
      if(elect_one()){
        const int col = f*FS;
        #pragma unroll
        for(int it=W9; it<NS; it++){
          mbar_wait(bar+8*(B_WEMPTY+it), 0);
          if(it==4) mbar_wait(bar+8*B_TD, 0);
          if(it==5) mbar_wait(bar+8*(B_HD+1), 0);
          if(it>=PACE) mbar_wait(bar+8*(B_WFULL+it-PACE), 0);
          mbar_expect_tx(bar+8*(B_WFULL+it), 22528);
          load_w_stage(maps, sb+OFF_W+(5-it)*WSLOT, col, ((it+(rt&14))&15)*32, bar+8*(B_WFULL+it));
          if(it<5) STAMP(24+it);
        }
        mbar_wait(bar+8*(B_INIT+1), 0);
        mbar_wait(bar+8*B_X03, 0); ldx(0,3);
        uint32_t wb = bar, dst = sb+OFF_W+5*WSLOT, ph = 1; int k0 = ((6+(rt&14))&15)*32;
        #pragma unroll 1
        for(int j=4; j<4+(10+SKW)/2; j++){
          mbar_wait(wb+8*B_WEMPTY, ph);
          mbar_expect_tx(wb, 22528);       load_w_stage(maps, dst, col, k0, wb);
          mbar_wait(wb+8*B_WEMPTY+8, ph);
          mbar_expect_tx(wb+8, 22528);     load_w_stage(maps, dst-WSLOT, col, k0+32, wb+8);
          if(j<8){ mbar_wait(bar+8*(B_XEMPTY+(j&3)), 0); ldx(0,j); }
          const int j1 = j-SKW/2;
          if(j1>=4 && j1<8){ if(j1==4) mbar_wait(bar+8*(B_FB+1), 0); mbar_wait(bar+8*(B_XEMPTY+NX+(j1&3)), 0); ldx(1,j1); }
          if(j==5) asm volatile("cp.async.bulk.prefetch.L2.global [%0], 11008;"::"l"(wdn+b*5504):"memory");
          const bool wrap = wb==bar+32;
          wb = wrap? bar : wb+16; dst = wrap? dst+4*WSLOT : dst-2*WSLOT; ph ^= wrap; k0 = (k0+64)&511;
        }
        #pragma unroll
        for(int j=0;j<8;j++){
          constexpr int I0=16+SKW;
          const int slot=(I0+j)%NS, ci=(G2_CH>>(4*j))&3, kh=((G2_PEER>>j)&1)^rank;
          mbar_wait(bar+8*(B_WEMPTY+slot), ((I0+j)/NS)&1);
          mbar_expect_tx(bar+8*(B_WFULL+slot), 22528);
          tma2d(sb+OFF_W+(5-slot)*WSLOT, &maps.wd, rank*256+((fp+ci)&3)*64, (2*fp+kh)*FS, bar+8*(B_WFULL+slot));
        }
      }
      __syncwarp();
    } else if(warp==11){
      if(elect_one()) first_x(maps, sb, 0);
      __syncwarp();
      STAMP(63);
      mbar_wait(bar+8*(B_INIT+1), 0);
      __nanosleep(CSLEEP);
      STAMP(31);
      {
        const int j = rt*6+(lane>>2);
        float4 c = make_float4(0.f,0.f,0.f,0.f);
        if(lane<24 && j<88) c = gather_sum(&g_csp[(f*16+(lane&3)*4)*88+j], 4, 88, par);
        __syncwarp();
        #pragma unroll
        for(int o=1;o<4;o<<=1){ c.x+=__shfl_xor_sync(~0u,c.x,o); c.y+=__shfl_xor_sync(~0u,c.y,o); c.z+=__shfl_xor_sync(~0u,c.z,o); c.w+=__shfl_xor_sync(~0u,c.w,o); }
        if(lane<24 && j<88 && !(lane&3)) st_rlx128(&g_cs2[f*96+j], (__float_as_uint(c.x)&~1u)|par, __float_as_uint(c.y), __float_as_uint(c.z), __float_as_uint(c.w));
      }
      STAMP(29);
      { uint4 v[3]; int n=0; const int j2 = lane<24? lane+64 : lane;
        do{ __nanosleep(CSLEEP); ld_rlx128(&g_cs2[f*96+lane], v[0]); ld_rlx128(&g_cs2[f*96+lane+32], v[1]); ld_rlx128(&g_cs2[f*96+j2], v[2]); spin_guard(++n); }while(((v[0].x^par)|(v[1].x^par)|(v[2].x^par))&1);
        *(uint4*)(smem_raw+OFF_CS+lane*16)=v[0]; *(uint4*)(smem_raw+OFF_CS+(lane+32)*16)=v[1]; *(uint4*)(smem_raw+OFF_CS+j2*16)=v[2]; }
      mbar_wait(bar+8*(B_FB+1), 0);
      __syncwarp();
      if(lane<2) mbar_arrive(bar+8*(B_PAR+lane));
      STAMP(74);
      #pragma unroll 4
      for(int i=0;i<32;i++) g_xa[cb*1024+i*32+lane]=make_uint4(0,0,0,0);
    } else {
      const int w = warp-9;
      mbar_wait(bar+8*(B_HD+w), 0);
      STAMP(67+w*3);
      if(elect_one()){
        signal_add(&g_cnt[32+32*w]); STAMP(68+w*3);
        unsigned v; int n=0; do{ asm volatile("ld.acquire.gpu.global.u32 %0, [%1];":"=r"(v):"l"(&g_cnt[32+32*w]):"memory"); spin_guard(++n); }while((int)(v-epoch*128)<0);
        STAMP(7+w*16);
        asm volatile("fence.proxy.async.global;":::"memory");
        if(w) ldx(1,3); else mbar_arrive(bar+8*B_X03);
        mbar_arrive(bar+8*(B_FB+w));
      }
      __syncwarp();
      mbar_wait(bar+8*(B_RT+w), 0);
      {
        __nanosleep(CSLEEP);
        const float4 st=gather_sum(&g_stat[((rt*2+w)*8)*32+lane], 8, 32, par);
        const float s0=st.x, q0=st.y, s1=st.z, q1=st.w;
        const float m0=s0*(1.f/512), m1=s1*(1.f/512);
        const float v0=fmaxf(q0*(1.f/512)-m0*m0,0.f), v1=fmaxf(q1*(1.f/512)-m1*m1,0.f);
        const float r0=ln_rstd(v0), r1=ln_rstd(v1);
        *(float4*)(smem_raw+OFF_ROW+w*512+lane*16)=make_float4(-rbf(m0),r0,-rbf(m1),r1);
        __syncwarp();
        if(lane==0) mbar_arrive(bar+8*(B_PAR+w));
        STAMP(75+w);
      }
      STAMP(77+w);
    }
  } else {
    if(elect_one()){
      mbar_init(bar+8*(B_Q+warp),1);
      asm volatile("fence.proxy.async.shared::cta;":::"memory");
      mbar_expect_tx(bar+8*(B_Q+warp), 2048);
      const bf16* qp = q + pos2row((1-wg)*1024+b*8+(warp&3)*2)*512;
      bulk_g2s(sb+OFF_Q+2*warp*QP, qp, 1024, bar+8*(B_Q+warp)); bulk_g2s(sb+OFF_Q+(2*warp+1)*QP, qp-16*512, 1024, bar+8*(B_Q+warp));
    }
    __syncwarp();
    asm volatile("setmaxnreg.inc.sync.aligned.u32 224;");
    if(elect_one()){
      mbar_init(bar+8*(B_U+warp),1); mbar_expect_tx(bar+8*(B_U+warp), 2048);
      mbar_init(bar+8*(B_XFULL+warp),1); mbar_init(bar+8*(B_XEMPTY+warp),8);
      mbar_init(bar+8*(B_KV+warp),1);
      if(warp<NS){ mbar_init(bar+8*(B_WFULL+warp),1); mbar_init(bar+8*(B_WEMPTY+warp),8); mbar_init(bar+8*(B_ONE+warp),1); }
      else { const int i=warp-6; mbar_init(bar+8*(B_PRDY+i),4); mbar_init(bar+8*(B_RT+i),1); mbar_init(bar+8*(B_AFULL+i),1); mbar_expect_tx(bar+8*(B_AFULL+i), 22528); mbar_init(bar+8*(B_PAR+i),2); mbar_init(bar+8*(B_HD+i),8+i); if(i){ mbar_init(bar+8*B_SK,1); mbar_init(bar+8*B_SC,1); mbar_init(bar+8*B_X03,1); } else { mbar_init(bar+8*B_QD,8); mbar_init(bar+8*B_TD,3); } }
      asm volatile("fence.mbarrier_init.release.cluster;":::"memory");
    }
    __syncwarp();
    STAMP(56);
    const int wq = warp&3, g = lane>>2, t = lane&3;
    if(tid<8){ sts128(sb+OFF_U+tid*UPL+128*16, 0,0,0,0); }
    if(tid<128) sts128(sb+OFF_ZB+tid*16, 0,0,0,0);
    if(tid<12){ sts128(sb+OFF_TBL+(tid&3)*TBL+(tid>>2)*16, 0,0,0,0); }
    asm volatile("bar.sync 0;":::"memory");
    asm volatile("barrier.cluster.arrive.relaxed.aligned;":::"memory");
    STAMP(57);
    #pragma unroll
    for(int i=0;i<4;i++) mbar_wait(bar+8*(B_Q+wg*4+i), 0);
    STAMP(92+wg);
    {
      const uint32_t la = sb+OFF_Q+(wg*8+2*(lane>>3)+(lane&1))*QP + ((lane&7)>>1)*16 + wq*256;
      uint4 tv[4]; uint32_t w[2][8];
      const int irow = wq*32+t*2+(g>>2);
      const uint32_t dst = sb+OFF_IMG+irow*128+(((((g&3)+4*wg)^(b&7))^(irow&7))<<4);
      #pragma unroll
      for(int i=0;i<4;i++) ldsm4t(la+i*64, tv[i].x,tv[i].y,tv[i].z,tv[i].w);
      #pragma unroll
      for(int i=0;i<4;i++) sts128(dst+i*1024, max(~tv[i].x,1u),tv[i].y,tv[i].z,tv[i].w);
      asm volatile("fence.proxy.async.shared::cta;":::"memory");
      __syncwarp();
      if(lane==0) mbar_arrive(bar+8*B_QD);
      if(wg==0) STAMP(44);
      const uint32_t qa = sb+OFF_Q+(2*warp)*QP+lane*16;
      #pragma unroll
      for(int r=0;r<2;r++){ lds128_nm(qa+r*QP, w[r][0],w[r][1],w[r][2],w[r][3]); lds128_nm(qa+r*QP+512, w[r][4],w[r][5],w[r][6],w[r][7]); }
      float s[2], d[2];
      #pragma unroll
      for(int r=0;r<2;r++){
        float s0=0.f,s1=0.f,d0=0.f,d1=0.f;
        #pragma unroll
        for(int i=0;i<8;i++){ const float lo=bf_lo(w[r][i]), hi=bf_hi(w[r][i]); s0+=lo; s1+=hi; d0=fmaf(lo,lo,d0); d1=fmaf(hi,hi,d1); }
        s[r]=s0+s1; d[r]=d0+d1;
      }
      const bool u=lane&16, v=lane&8;
      const float a0=(u? s[1]:s[0])+__shfl_xor_sync(~0u,u? s[0]:s[1],16), a1=(u? d[1]:d[0])+__shfl_xor_sync(~0u,u? d[0]:d[1],16);
      float c0=(v? a1:a0)+__shfl_xor_sync(~0u,v? a0:a1,8);
      c0+=__shfl_xor_sync(~0u,c0,4); c0+=__shfl_xor_sync(~0u,c0,2); c0+=__shfl_xor_sync(~0u,c0,1);
      const float m=c0*(1.f/512), sq=__shfl_down_sync(~0u,c0,8);
      const float rs=ln_rstd(fmaxf(fmaf(-m,m,sq*(1.f/512)),0.f)), rh=rbf(rs);
      const float m1=__shfl_down_sync(~0u,m,16), rs1=__shfl_down_sync(~0u,rs,16), rh1=rbf(rs1);
      mbar_wait(bar+8*B_SC, 0);
      if(lane==0){ st_rlx128(&g_qs[b*8+(warp^(b&7))], pack_bf16(m,m1), pack_bf16(rh,rh1), pack_bf16(rs-rh,rs1-rh1), lds32(sb+OFF_MISC)); }
      __syncwarp();
      if(wg==0) STAMP(46);
    }
    mbar_wait(bar+8*B_SK, 0);
    STAMP(90+wg);
    {
      const int Q = tid+2;
      const uint32_t ta = sb+OFF_TBL+((Q*32)^(((Q>>2)&3)<<5));
      const bool sw2 = (Q>>2)&1;
      uint4 kq[4]; uint32_t kn[4];
      #pragma unroll
      for(int i=0;i<4;i++){ lds128_nm(sb+OFF_SK+i*4096+tid*16, kq[i].x,kq[i].y,kq[i].z,kq[i].w); kn[i] = lds32(sb+OFF_SK+i*4096+(warp+1)*512); }
      if(tid==0){
        const uint32_t d01=lds32(sb+OFF_MISC+4), d23=lds32(sb+OFF_MISC+8);
        kq[0].x=hadd2_bf16(kq[0].x,d01&0xffffu); kq[1].x=hadd2_bf16(kq[1].x,d01>>16); kq[2].x=hadd2_bf16(kq[2].x,d23&0xffffu); kq[3].x=hadd2_bf16(kq[3].x,d23>>16);
      }
      __syncwarp();
      #pragma unroll
      for(int i=0;i<4;i++){
        uint32_t nx = __shfl_down_sync(~0u, kq[i].x, 1); if(lane==31) nx = kn[i];
        const uint4 o = make_uint4(__byte_perm(kq[i].x,kq[i].y,0x5432), __byte_perm(kq[i].y,kq[i].z,0x5432), __byte_perm(kq[i].z,kq[i].w,0x5432), __byte_perm(kq[i].w,nx,0x5432));
        const uint4 f0 = sw2? o:kq[i], f1 = sw2? kq[i]:o;
        sts128(ta+i*TBL+(sw2?16:0), f0.x,f0.y,f0.z,f0.w);
        sts128(ta+i*TBL+(sw2?0:16), f1.x,f1.y,f1.z,f1.w);
        if(tid==0) sts128(sb+OFF_TBL+i*TBL+48, 0,0,0, kq[i].x<<16);
      }
      __syncwarp();
      if(lane<3) mbar_arrive(bar+8*(B_WEMPTY+(lane==2? 4:lane)));
      asm volatile("bar.sync 1, 256;":::"memory");
    }
    STAMP(80+wg);
    STAMP(82+wg);
    asm volatile("barrier.cluster.wait.aligned;":::"memory");
    bool x_ok = false;
    {
      const int c=lane>>3, p=g&1;
      uint32_t tb[5];
      #pragma unroll
      for(int s=0;s<5;s++){ const int y=16*c+wq+t+p+4*s; const int id=8*(y>>2)+4*(1-p)+(y&3); tb[s]=sb+OFF_TBL+wg*2*TBL+((id^(((id>>5)&3)<<3))<<2); }
      uint64_t du = make_desc(sb+OFF_U+wg*2*UCH, UPL, 128, 0);
      float aE[2][32], aL[2][32];
      uint32_t R[2][4][8], oku=0; uint4 xr[4], st[8], ar[2];
#define P_TY(K) ((K)>=8 ? 2 : (K)&1)
#define P_LV(K) ((K)>=8 ? (K)-8 : (K)>>1)
#define P_MA(K) ((P_TY(K)==1 ? 15 : 7) - 2*P_LV(K))
#define P_N(K,M) (P_TY(K)==2 ? 64 : P_TY(K)==1 ? 128-8*(M) : 64-8*(M))
#define P_B(K,M) (8*(M) + (P_TY(K)==0 ? 64 : 0))
#define P_LD(K,J) conv_lda(R[(K)&1][J],tb,((J)&1)*TBL+(P_MA(K)-((J)>>1))*512)
#define P_MMA(K,J) conv_mma<P_N(K,P_MA(K)-((J)>>1))>(P_TY(K)==0? aE[(J)&1]:aL[(J)&1], R[(K)&1][J], du+((J)&1)*(UCH/16)+P_B(K,P_MA(K)-((J)>>1)))
#define CONV_PREP(K) { if constexpr(P_TY(K)!=1) oku = mbar_test(bar+8*(B_U+P_LV(K)+(P_TY(K)?4:0)),0); P_LD(K,0); P_LD(K,1); P_LD(K,2); P_LD(K,3); }
#define CONV_PAIR(K) { \
        _Pragma("unroll") for(int j=0;j<4;j++) conv_dup(R[(K)&1][j]); \
        if constexpr(P_TY(K)<2){ _Pragma("unroll") for(int i=0;i<2;i++){ float* a_=(P_TY(K)==0? aE[i]:aL[i])+8*P_LV(K); zero4(a_); zero4(a_+4); } } \
        if constexpr(P_TY(K)!=1){ if(!oku) mbar_wait(bar+8*(B_U+P_LV(K)+(P_TY(K)?4:0)),0); asm volatile("fence.proxy.async.shared::cta;":::"memory"); } \
        asm volatile("" : "+l"(du)); \
        PP_SYNC(); \
        if constexpr((K)==0||(K)==6||(K)==7||(K)==11){ if(wg==0) STAMP(96+(K)); } \
        wg_fence(); \
        P_MMA(K,0); P_MMA(K,1); \
        if constexpr(P_TY(K)<2){ wg_commit(); wg_fence(); } \
        P_MMA(K,2); P_MMA(K,3); \
        wg_commit(); \
        if((K)<11 || wg==0) PP_ARRIVE(); \
        if constexpr((K)<11){ if constexpr((K)>0){ if constexpr(P_TY(K)<2) wg_wait<2>(); else wg_wait<1>(); } if constexpr((K)!=6) CONV_PREP((K)+1) } }
#define PP_SYNC() asm volatile("bar.sync %0, 256;"::"r"(2+wg):"memory")
#define PP_ARRIVE() asm volatile("bar.arrive %0, 256;"::"r"(3-wg):"memory")
      if(wg==1) PP_ARRIVE();
      CONV_PREP(0) CONV_PAIR(0) CONV_PAIR(1) CONV_PAIR(2) CONV_PAIR(3) CONV_PAIR(4) CONV_PAIR(5)
      mbar_wait(bar+8*B_XA,0);
      wg_wait<0>();
      load_xs(xr,st,sb,warp,lane); check_xs(xr,st,lds32(sb+OFF_MISC),sb,warp); ln_x(xr+2,st+4,ar);
      if(lane==0) mbar_arrive(bar+8*(B_WEMPTY+3));
      CONV_PAIR(6)
      if(lane==0) mbar_arrive(bar+8*(B_WEMPTY+2));
      wg_wait<0>();
      conv_put<1>(aE[0],aE[1],sb,warp,lane);
      CONV_PREP(7)
      conv_get<1>(xr+2,ar,sb,warp,lane);
      __syncwarp();
      if(lane==0) mbar_arrive(bar+8*B_HD);
      STAMP(84+wg);
      CONV_PAIR(7) CONV_PAIR(8) CONV_PAIR(9) CONV_PAIR(10) CONV_PAIR(11)
      ln_x(xr,st,ar);
      if(wg==0 && mbar_test(bar+8*B_XFULL, 0)) x_ok = !x_bad(sb, 0, wq, lane);
      wg_wait<0>();
      STAMP(86+wg);
      conv_put<0>(aL[0],aL[1],sb,warp,lane);
      conv_get<0>(xr,ar,sb,warp,lane);
      __syncwarp();
      if(lane==0){ mbar_arrive(bar+8*(B_HD+1)); mbar_arrive(bar+8*(B_WEMPTY+5)); }
      STAMP(88+wg);
    }
    if(wg==1 && wq<3){
      mbar_wait(bar+8*(B_WFULL+SKW+(rt&1)), 0);
      const int j = tid-128;
      const uint32_t par = lds32(sb+OFF_MISC)&1;
      float c0=0.f,c1=0.f,c2=0.f,c3=0.f;
      const uint32_t cb = sb+OFF_W+(5-SKW-(rt&1))*WSLOT+wq*8192+t*4+maps.upfirst*4096;
      #pragma unroll CSU
      for(int k=0;k<32;k++){
        const uint32_t ad = cb + k*128 + ((g^(k&7))<<4);
        const uint32_t v=lds32(ad), u=lds32(ad+4096-maps.upfirst*8192); c0+=bf_lo(v); c1+=bf_hi(v); c2+=bf_lo(u); c3+=bf_hi(u);
      }
      if(j<88) st_rlx128(&g_csp[(f*16+rt)*88+j], (__float_as_uint(c0)&~1u)|par, __float_as_uint(c1), __float_as_uint(c2), __float_as_uint(c3));
      __syncwarp();
      STAMP(73);
    }
    if(warp==7){ if(elect_one()){ first_x(maps, sb, 1); mbar_arrive(bar+8*(B_INIT+1)); } __syncwarp(); STAMP(94); }
    const uint32_t xempty_cl = mapa(bar+8*(B_XEMPTY+wg*NX), lane&1);
    float ag[88], au[88];
    const uint32_t xbase = sb+OFF_X+wg*NX*XSLOT, rbase = sb+(wg? OFF_RES1:OFF_RES0);
    const uint32_t rfrag = rbase+((lane&7)+8*(lane>>4))*128+(((2*wq+((lane>>3)&1))^(lane&7))<<4);
    constexpr uint64_t DHI_A = (uint64_t)0x40000040u<<32, DHI_B = DHI_A | (512u<<16);
    const uint32_t og = maps.upfirst*256, ou = 256-og;
    uint32_t wb = bar+8*wg*(SKW%NS), ph = wg*(SKW/NS), dbl = (((sb+OFF_W+(5-wg*(SKW%NS))*WSLOT)&0x3FFFF)>>4), dal = (xbase&0x3FFFF)>>4, xb = bar+8*(B_XFULL+wg*NX), pwb = 0;
    uint32_t relm = lane==0? 0xff : lane==1? (wg? (0xff00>>(SKW/2))&0xff : (1<<(SKW/2))-1) : 0;
#define G1_STAGE(DA,DB,ACC) { wg_fence(); wgmma_ss<176,1,1>(ag, DA, DHI_B|((DB)+og), ACC); wgmma_ss<176,1,1>(au, DA, DHI_B|((DB)+ou), ACC); wgmma_ss<176,1,1>(ag, (DA)+128, DHI_B|((DB)+og+128), 1); wgmma_ss<176,1,1>(au, (DA)+128, DHI_B|((DB)+ou+128), 1); wg_commit(); }
    {
      mbar_wait(wb, ph);
      if(!x_ok){
        mbar_wait(xb, 0);
        STAMP(wg? 47:45);
        if(x_bad(sb, wg, wq, lane)){
          const uint32_t par = lds32(sb+OFF_MISC), co = lane*128+(((2*wq)^(lane&7))<<4);
          #pragma unroll 1
          for(int tl=0;tl<4;tl++){
            const bf16* src = g_hT+((tl<3? ((rt>>1)+wg*(SKW/2)+tl)&7 : rank*4+fp)*64+lane)*2048+wg*1024+rt*64+wq*16;
            uint4 v[4]; int n=0;
            do{
              #pragma unroll
              for(int i=0;i<4;i++) ld_rlx128(src+(i>>1)*32*2048+(i&1)*8, v[i]);
            }while((((v[0].x^par)|(v[1].x^par)|(v[2].x^par)|(v[3].x^par))&1) && ++n<2000000);
            #pragma unroll
            for(int i=0;i<4;i++) sts128(((tl<3? xbase+tl*8192 : rbase)+(i>>1)*4096+co)^((i&1)<<4), v[i].x,v[i].y,v[i].z,v[i].w);
          }
          asm volatile("fence.proxy.async.shared::cta;":::"memory");
          __syncwarp();
        }
      }
      STAMP(1+wg*16);
      #pragma unroll
      for(int i=0;i<88;i++){ ag[i]=0.f; au[i]=0.f; }
      G1_STAGE(DHI_A|dal, dbl, 0)
    }
    uint32_t okb = mbar_test(wb+8, ph);
    #pragma unroll 1
    for(int xi=0; xi<8; xi++){
      if(!okb) mbar_wait(wb+8, ph);
      G1_STAGE(DHI_A|(dal+256), dbl-WSLOT/16, 1)
      pwb = wb;
      const bool wrap = wb==bar+8*4;
      wb = wrap? bar : wb+16; dbl = wrap? dbl+4*(WSLOT/16) : dbl-2*(WSLOT/16); ph ^= wrap;
      dal = (xi==3)? dal-3*512 : dal+512; xb = (xi==3)? xb-24 : xb+8;
      const uint32_t oka = mbar_test(xb, xi>=3) & mbar_test(wb, ph);
      if(xi==(wg? STX1:STX0)){
        float s0=0.f,s1=0.f,q0=0.f,q1=0.f;
        #pragma unroll
        for(int kk=0;kk<4;kk++){
          uint32_t r[4]; ldsm4t(rfrag+kk*2048, r[0],r[1],r[2],r[3]);
          #pragma unroll
          for(int i=0;i<4;i++){ const float lo=bf_lo(r[i]), hi=bf_hi(r[i]); if(i&1){ s1+=lo+hi; q1=fmaf(lo,lo,fmaf(hi,hi,q1)); } else { s0+=lo+hi; q0=fmaf(lo,lo,fmaf(hi,hi,q0)); } }
        }
        #pragma unroll
        for(int o=1;o<4;o<<=1){ s0+=__shfl_xor_sync(~0u,s0,o); q0+=__shfl_xor_sync(~0u,q0,o); s1+=__shfl_xor_sync(~0u,s1,o); q1+=__shfl_xor_sync(~0u,q1,o); }
        if(t==0) st_rlx128(&g_stat[((rt*2+wg)*8+f)*32+wq*8+g], (__float_as_uint(s0)&~1u)|(lds32(sb+OFF_MISC)&1), __float_as_uint(q0), __float_as_uint(s1), __float_as_uint(q1));
        __syncwarp();
        if(tid==wg*128) mbar_arrive(bar+8*(B_RT+wg));
      }
      uint32_t rel = relm&1; relm>>=1; uint32_t xpar = xi>=3;
      asm volatile("":"+r"(rel),"+r"(xpar));
      wg_wait<1>();
      if(rel) mbar_arrive(pwb+8*B_WEMPTY);
      if(xi==7) break;
      if(!oka){ mbar_wait(xb, xpar); mbar_wait(wb, ph); }
      G1_STAGE(DHI_A|dal, dbl, 1)
      okb = mbar_test(wb+8, ph);
      wg_wait<1>();
      if(rel) mbar_arrive(pwb+8*B_WEMPTY+8);
      if((lane>>1)==1 && xi<4) mbar_arrive_cl(xempty_cl+8*xi);
      if(xi==6 && lane==0) mbar_arrive_cl(mapa(bar+8*(B_PRDY+wg), rank^1));
    }
    mbar_wait(bar+8*(B_PAR+wg), 0);
    mbar_wait(bar+8*(B_PRDY+wg), 0);
    const float4 p0=*(const float4*)(smem_raw+OFF_ROW+(wg*32+wq*8+g)*16);
    const float nm0=p0.x, r0=p0.y, nm1=p0.z, r1=p0.w;
    wg_wait<0>();
    STAMP(2+wg*16);
    if(lane==0){ mbar_arrive_n(pwb+8*B_WEMPTY+8, (wg && SKW)? 2:1); }
    uint32_t act[44], actp[44];
    const float sc0=0.5f*r0*r0, sc1=0.5f*r1*r1;
    const uint32_t adst = mapa(xbase+wq*6144+lane*16, rank^1), abar = mapa(bar+8*(B_AFULL+wg), rank^1);
    {
      const float4* cs = (const float4*)(smem_raw+OFF_CS);
      const float h0=0.5f*r0, h1=0.5f*r1;
      #pragma unroll
      for(int j=0;j<22;j++){
        const float4 c4=cs[4*j+t];
        const float g0=fmaf(nm0,c4.x,ag[4*j+0]), g1=fmaf(nm0,c4.y,ag[4*j+1]), g2=fmaf(nm1,c4.x,ag[4*j+2]), g3=fmaf(nm1,c4.y,ag[4*j+3]);
        const float y0=g0*fmaf(nm0,c4.z,au[4*j+0]), y1=g1*fmaf(nm0,c4.w,au[4*j+1]), y2=g2*fmaf(nm1,c4.z,au[4*j+2]), y3=g3*fmaf(nm1,c4.w,au[4*j+3]);
        act[2*j]  =pack_bf16(fmaf(y0,tanh_fast(g0*h0),y0), fmaf(y1,tanh_fast(g1*h0),y1));
        act[2*j+1]=pack_bf16(fmaf(y2,tanh_fast(g2*h1),y2), fmaf(y3,tanh_fast(g3*h1),y3));
        if((j%3)==2 && j/3<NIN){ const int kk=j/3; st_async128(adst+kk*512, act[4*kk],act[4*kk+1],act[4*kk+2],act[4*kk+3], abar); }
      }
    }
    STAMP(3+wg*16);
    #pragma unroll
    for(int kk=NIN;kk<11;kk++) st_async128(adst+kk*512, act[4*kk],act[4*kk+1],act[4*kk+2],act[4*kk+3], abar);
    float acc2[2][32];
    #pragma unroll
    for(int i=0;i<32;i++){ acc2[0][i]=0.f; acc2[1][i]=0.f; }
    const uint32_t wbase = xbase+wq*6144, wlast = xbase+3*XSLOT+wq*2048;
    const uint32_t srow = ((~lane&4)<<1) | ((~lane&1)<<2) | (lane&2) | ((lane>>3)&1);
    const int orow = pos2row(wg*1024+rt*64+wq*16+5);
    uint32_t hr[16];
    #pragma unroll
    for(int kk=0;kk<4;kk++) ldsm4t(rfrag+kk*2048, hr[4*kk],hr[4*kk+1],hr[4*kk+2],hr[4*kk+3]);
    auto stage=[&](const float* a, int c){
      #pragma unroll
      for(int kk=0;kk<4;kk++){
        uint32_t o0=pack_bf16(a[8*kk]*sc0,a[8*kk+1]*sc0), o1=pack_bf16(a[8*kk+2]*sc1,a[8*kk+3]*sc1), o2=pack_bf16(a[8*kk+4]*sc0,a[8*kk+5]*sc0), o3=pack_bf16(a[8*kk+6]*sc1,a[8*kk+7]*sc1);
        if(c==0){
          o0=hadd2_bf16(o0,hr[4*kk]); o1=hadd2_bf16(o1,hr[4*kk+1]); o2=hadd2_bf16(o2,hr[4*kk+2]); o3=hadd2_bf16(o3,hr[4*kk+3]);
        }
        stsm4_nm((c<3? wbase+c*2048 : wlast)+srow*128+(((2*kk+(lane>>4))^(srow&7))<<4), o0,o1,o2,o3);
      }
    };
    auto flush=[&](int c, int n){
      asm volatile("fence.proxy.async.shared::cta;":::"memory");
      __syncwarp();
      if(elect_one()){
        #pragma unroll
        for(int i=0;i<n;i++) tma4d_red_add(&maps.out, rank*256+((fp+c+i)&3)*64, orow&7, (orow>>3)&15, orow>>7, c+i<3? wbase+(c+i)*2048 : wlast);
        asm volatile("cp.async.bulk.commit_group;":::"memory");
      }
    };
    uint32_t okw = 0;
    #pragma unroll
    for(int i=0;i<8;i++){
      const int ch = (G2_CH>>(4*i))&3, peer = (G2_PEER>>i)&1;
      constexpr int S0=(16+SKW)%NS, P0=((16+SKW)/NS)&1;
      const int slot=(S0+i)%NS, pslot=(S0+i+NS-1)%NS, ph=(P0+(S0+i)/NS)&1;
      if(i==2){
        mbar_wait(bar+8*(B_AFULL+wg), 0);
        #pragma unroll
        for(int kk=0;kk<11;kk++) lds128_nm(wbase+lane*16+kk*512, actp[4*kk],actp[4*kk+1],actp[4*kk+2],actp[4*kk+3]);
      }
      if(!okw) mbar_wait(bar+8*(B_WFULL+slot), ph);
      if(i<7) okw = mbar_test(bar+8*(B_WFULL+(S0+i+1)%NS), (P0+(S0+i+1)/NS)&1);
      if(i==2 || i==4 || i==6 || (i==0 && wg==1)) asm volatile("bar.sync %0, 256;"::"r"(2+wg):"memory");
      const uint64_t db = make_desc(sb+OFF_W+(5-slot)*WSLOT, 0, 1024, 1);
      wg_fence();
      #pragma unroll
      for(int kk=0;kk<11;kk++){
        if(peer) wgmma_rs<64,1>(acc2[ch&1], actp[4*kk],actp[4*kk+1],actp[4*kk+2],actp[4*kk+3], db+kk*128, 1);
        else     wgmma_rs<64,1>(acc2[ch&1], act[4*kk],act[4*kk+1],act[4*kk+2],act[4*kk+3], db+kk*128, kk>0);
      }
      wg_commit();
      if(i==1 || i==3 || i==5 || (i==7 && wg==0)) asm volatile("bar.arrive %0, 256;"::"r"(3-wg):"memory");
      if(i==1){ wg_wait<0>(); if(lane<2) mbar_arrive(bar+8*(B_WEMPTY+(lane? slot:pslot))); }
      if(i==3){ wg_wait<1>(); stage(acc2[0], 0); flush(0,1); wg_wait<0>(); stage(acc2[1], 1); flush(1,1); }
      if(i==5){ wg_wait<0>(); stage(acc2[0], 2); flush(2,1); }
      STAMP(32+wg*16+i);
    }
    wg_wait<0>();
    STAMP(4+wg*16);
    stage(acc2[1], 3); flush(3,1);
    STAMP(5+wg*16);
    asm volatile("cp.async.bulk.wait_group.read 0;":::"memory");
    STAMP(6+wg*16);
  }
  __syncwarp();
  asm volatile("barrier.cluster.arrive.relaxed.aligned;":::"memory");
  asm volatile("barrier.cluster.wait.aligned;":::"memory");
}

typedef CUresult (*PFN_encodeTiled)(CUtensorMap*, CUtensorMapDataType, cuuint32_t, void*, const cuuint64_t*, const cuuint64_t*, const cuuint32_t*, const cuuint32_t*, CUtensorMapInterleave, CUtensorMapSwizzle, CUtensorMapL2promotion, CUtensorMapFloatOOBfill);
static void make2d(PFN_encodeTiled enc, CUtensorMap* m, const void* p, uint64_t d0, uint64_t d1, uint32_t b0, uint32_t b1){
  cuuint64_t gd[2]={d0,d1}; cuuint64_t gs[1]={d0*2}; cuuint32_t bx[2]={b0,b1}; cuuint32_t es[2]={1,1};
  enc(m,CU_TENSOR_MAP_DATA_TYPE_BFLOAT16,2,(void*)p,gd,gs,bx,es,CU_TENSOR_MAP_INTERLEAVE_NONE,CU_TENSOR_MAP_SWIZZLE_128B,CU_TENSOR_MAP_L2_PROMOTION_L2_128B,CU_TENSOR_MAP_FLOAT_OOB_FILL_NONE);
}
static void make3d(PFN_encodeTiled enc, CUtensorMap* m, const void* p, uint64_t d0, uint64_t d1, uint64_t d2, uint64_t s1, uint64_t s2, uint32_t b0, uint32_t b1, uint32_t b2, CUtensorMapSwizzle sw, CUtensorMapL2promotion pr){
  cuuint64_t gd[3]={d0,d1,d2}; cuuint64_t gs[2]={s1,s2}; cuuint32_t bx[3]={b0,b1,b2}; cuuint32_t es[3]={1,1,1};
  enc(m,CU_TENSOR_MAP_DATA_TYPE_BFLOAT16,3,(void*)p,gd,gs,bx,es,CU_TENSOR_MAP_INTERLEAVE_NONE,sw,pr,CU_TENSOR_MAP_FLOAT_OOB_FILL_NONE);
}

extern "C" void kernel_launch(void* const* d_in, const int* in_sizes, int n_in, void* d_out, int out_size){
  const bf16* q=(const bf16*)d_in[0]; const bf16* k=(const bf16*)d_in[1]; const bf16* v=(const bf16*)d_in[2];
  const bf16* sh=(const bf16*)d_in[3]; const bf16* K=(const bf16*)d_in[4]; const bf16* Dv=(const bf16*)d_in[5];
  const bf16* wgt=(const bf16*)d_in[7]; const bf16* wup=(const bf16*)d_in[8]; const bf16* wdn=(const bf16*)d_in[9];
  void* fn=nullptr; cudaDriverEntryPointQueryResult qr; cudaGetDriverEntryPoint("cuTensorMapEncodeTiled",&fn,cudaEnableDefault,&qr);
  PFN_encodeTiled enc=(PFN_encodeTiled)fn;
  void* hT; cudaGetSymbolAddress(&hT,g_hT);
  Maps maps;
  make3d(enc,&maps.k,k,512,256,8,8192,1024,8,17,8,CU_TENSOR_MAP_SWIZZLE_NONE,CU_TENSOR_MAP_L2_PROMOTION_L2_128B);
  make3d(enc,&maps.v,v,512,256,8,8192,1024,8,16,8,CU_TENSOR_MAP_SWIZZLE_NONE,CU_TENSOR_MAP_L2_PROMOTION_L2_128B);
  { maps.upfirst = wup<wgt; const bf16* w0 = wup<wgt? wup:wgt; const uint64_t dm = (uint64_t)((wup<wgt? wgt-wup : wup-wgt)*2);
    cuuint64_t gd[4]={F_,D_,2,2}; cuuint64_t gs[3]={F_*2,dm,128}; cuuint32_t bx[4]={64,32,2,2}; cuuint32_t es[4]={1,1,1,1};
    enc(&maps.w64,CU_TENSOR_MAP_DATA_TYPE_BFLOAT16,4,(void*)w0,gd,gs,bx,es,CU_TENSOR_MAP_INTERLEAVE_NONE,CU_TENSOR_MAP_SWIZZLE_128B,CU_TENSOR_MAP_L2_PROMOTION_L2_128B,CU_TENSOR_MAP_FLOAT_OOB_FILL_NONE);
    make3d(enc,&maps.w48,w0,F_,D_,2,F_*2,dm,48,32,2,CU_TENSOR_MAP_SWIZZLE_128B,CU_TENSOR_MAP_L2_PROMOTION_L2_128B); }
  make2d(enc,&maps.wd,wdn,D_,F_,64,176);
  make2d(enc,&maps.ht,hT,S_,D_,64,32);
  { cuuint64_t gd[4]={512,8,16,16}; cuuint64_t gs[3]={1024,8192,131072}; cuuint32_t bx[4]={64,2,4,2}; cuuint32_t es[4]={1,1,1,1};
    enc(&maps.out,CU_TENSOR_MAP_DATA_TYPE_BFLOAT16,4,d_out,gd,gs,bx,es,CU_TENSOR_MAP_INTERLEAVE_NONE,CU_TENSOR_MAP_SWIZZLE_128B,CU_TENSOR_MAP_L2_PROMOTION_NONE,CU_TENSOR_MAP_FLOAT_OOB_FILL_NONE); }
  void* xa; cudaGetSymbolAddress(&xa,g_xa);
  make2d(enc,&maps.xa,xa,8192,128,64,128);
  cudaFuncSetAttribute(fused_kernel,cudaFuncAttributeMaxDynamicSharedMemorySize,SMEM_BYTES);
  fused_kernel<<<128,384,SMEM_BYTES>>>(maps,q,sh,K,Dv,wgt,wup,wdn,(bf16*)d_out);
}
```

```cpp
#include <cuda_runtime.h>
#include <cuda_bf16.h>
#include <cuda.h>
#include <stdint.h>

template<int TA,int TB> __device__ __forceinline__ void wgmma_ss_n176(float* d, uint64_t da, uint64_t db, int sd){
  asm volatile("{ .reg .pred p; setp.ne.b32 p, %90, 0; wgmma.mma_async.sync.aligned.m64n176k16.f32.bf16.bf16 {%0,%1,%2,%3,%4,%5,%6,%7,%8,%9,%10,%11,%12,%13,%14,%15,%16,%17,%18,%19,%20,%21,%22,%23,%24,%25,%26,%27,%28,%29,%30,%31,%32,%33,%34,%35,%36,%37,%38,%39,%40,%41,%42,%43,%44,%45,%46,%47,%48,%49,%50,%51,%52,%53,%54,%55,%56,%57,%58,%59,%60,%61,%62,%63,%64,%65,%66,%67,%68,%69,%70,%71,%72,%73,%74,%75,%76,%77,%78,%79,%80,%81,%82,%83,%84,%85,%86,%87}, %88, %89, p, 1, 1, %91, %92; }"
   : "+f"(d[0]),"+f"(d[1]),"+f"(d[2]),"+f"(d[3]),"+f"(d[4]),"+f"(d[5]),"+f"(d[6]),"+f"(d[7]),"+f"(d[8]),"+f"(d[9]),"+f"(d[10]),"+f"(d[11]),"+f"(d[12]),"+f"(d[13]),"+f"(d[14]),"+f"(d[15]),"+f"(d[16]),"+f"(d[17]),"+f"(d[18]),"+f"(d[19]),"+f"(d[20]),"+f"(d[21]),"+f"(d[22]),"+f"(d[23]),"+f"(d[24]),"+f"(d[25]),"+f"(d[26]),"+f"(d[27]),"+f"(d[28]),"+f"(d[29]),"+f"(d[30]),"+f"(d[31]),"+f"(d[32]),"+f"(d[33]),"+f"(d[34]),"+f"(d[35]),"+f"(d[36]),"+f"(d[37]),"+f"(d[38]),"+f"(d[39]),"+f"(d[40]),"+f"(d[41]),"+f"(d[42]),"+f"(d[43]),"+f"(d[44]),"+f"(d[45]),"+f"(d[46]),"+f"(d[47]),"+f"(d[48]),"+f"(d[49]),"+f"(d[50]),"+f"(d[51]),"+f"(d[52]),"+f"(d[53]),"+f"(d[54]),"+f"(d[55]),"+f"(d[56]),"+f"(d[57]),"+f"(d[58]),"+f"(d[59]),"+f"(d[60]),"+f"(d[61]),"+f"(d[62]),"+f"(d[63]),"+f"(d[64]),"+f"(d[65]),"+f"(d[66]),"+f"(d[67]),"+f"(d[68]),"+f"(d[69]),"+f"(d[70]),"+f"(d[71]),"+f"(d[72]),"+f"(d[73]),"+f"(d[74]),"+f"(d[75]),"+f"(d[76]),"+f"(d[77]),"+f"(d[78]),"+f"(d[79]),"+f"(d[80]),"+f"(d[81]),"+f"(d[82]),"+f"(d[83]),"+f"(d[84]),"+f"(d[85]),"+f"(d[86]),"+f"(d[87]) : "l"(da), "l"(db), "r"(sd), "n"(TA), "n"(TB));
}
template<int TB> __device__ __forceinline__ void wgmma_rs_n8(float* d, uint32_t a0, uint32_t a1, uint32_t a2, uint32_t a3, uint64_t db, int sd){
  asm volatile("{ .reg .pred p; setp.ne.b32 p, %9, 0; wgmma.mma_async.sync.aligned.m64n8k16.f32.bf16.bf16 {%0,%1,%2,%3}, {%4,%5,%6,%7}, %8, p, 1, 1, %10; }"
   : "+f"(d[0]),"+f"(d[1]),"+f"(d[2]),"+f"(d[3]) : "r"(a0),"r"(a1),"r"(a2),"r"(a3), "l"(db), "r"(sd), "n"(TB));
}
template<int TB> __device__ __forceinline__ void wgmma_rs_n16(float* d, uint32_t a0, uint32_t a1, uint32_t a2, uint32_t a3, uint64_t db, int sd){
  asm volatile("{ .reg .pred p; setp.ne.b32 p, %13, 0; wgmma.mma_async.sync.aligned.m64n16k16.f32.bf16.bf16 {%0,%1,%2,%3,%4,%5,%6,%7}, {%8,%9,%10,%11}, %12, p, 1, 1, %14; }"
   : "+f"(d[0]),"+f"(d[1]),"+f"(d[2]),"+f"(d[3]),"+f"(d[4]),"+f"(d[5]),"+f"(d[6]),"+f"(d[7]) : "r"(a0),"r"(a1),"r"(a2),"r"(a3), "l"(db), "r"(sd), "n"(TB));
}
template<int TB> __device__ __forceinline__ void wgmma_rs_n24(float* d, uint32_t a0, uint32_t a1, uint32_t a2, uint32_t a3, uint64_t db, int sd){
  asm volatile("{ .reg .pred p; setp.ne.b32 p, %17, 0; wgmma.mma_async.sync.aligned.m64n24k16.f32.bf16.bf16 {%0,%1,%2,%3,%4,%5,%6,%7,%8,%9,%10,%11}, {%12,%13,%14,%15}, %16, p, 1, 1, %18; }"
   : "+f"(d[0]),"+f"(d[1]),"+f"(d[2]),"+f"(d[3]),"+f"(d[4]),"+f"(d[5]),"+f"(d[6]),"+f"(d[7]),"+f"(d[8]),"+f"(d[9]),"+f"(d[10]),"+f"(d[11]) : "r"(a0),"r"(a1),"r"(a2),"r"(a3), "l"(db), "r"(sd), "n"(TB));
}
template<int TB> __device__ __forceinline__ void wgmma_rs_n32(float* d, uint32_t a0, uint32_t a1, uint32_t a2, uint32_t a3, uint64_t db, int sd){
  asm volatile("{ .reg .pred p; setp.ne.b32 p, %21, 0; wgmma.mma_async.sync.aligned.m64n32k16.f32.bf16.bf16 {%0,%1,%2,%3,%4,%5,%6,%7,%8,%9,%10,%11,%12,%13,%14,%15}, {%16,%17,%18,%19}, %20, p, 1, 1, %22; }"
   : "+f"(d[0]),"+f"(d[1]),"+f"(d[2]),"+f"(d[3]),"+f"(d[4]),"+f"(d[5]),"+f"(d[6]),"+f"(d[7]),"+f"(d[8]),"+f"(d[9]),"+f"(d[10]),"+f"(d[11]),"+f"(d[12]),"+f"(d[13]),"+f"(d[14]),"+f"(d[15]) : "r"(a0),"r"(a1),"r"(a2),"r"(a3), "l"(db), "r"(sd), "n"(TB));
}
template<int TB> __device__ __forceinline__ void wgmma_rs_n40(float* d, uint32_t a0, uint32_t a1, uint32_t a2, uint32_t a3, uint64_t db, int sd){
  asm volatile("{ .reg .pred p; setp.ne.b32 p, %25, 0; wgmma.mma_async.sync.aligned.m64n40k16.f32.bf16.bf16 {%0,%1,%2,%3,%4,%5,%6,%7,%8,%9,%10,%11,%12,%13,%14,%15,%16,%17,%18,%19}, {%20,%21,%22,%23}, %24, p, 1, 1, %26; }"
   : "+f"(d[0]),"+f"(d[1]),"+f"(d[2]),"+f"(d[3]),"+f"(d[4]),"+f"(d[5]),"+f"(d[6]),"+f"(d[7]),"+f"(d[8]),"+f"(d[9]),"+f"(d[10]),"+f"(d[11]),"+f"(d[12]),"+f"(d[13]),"+f"(d[14]),"+f"(d[15]),"+f"(d[16]),"+f"(d[17]),"+f"(d[18]),"+f"(d[19]) : "r"(a0),"r"(a1),"r"(a2),"r"(a3), "l"(db), "r"(sd), "n"(TB));
}
template<int TB> __device__ __forceinline__ void wgmma_rs_n48(float* d, uint32_t a0, uint32_t a1, uint32_t a2, uint32_t a3, uint64_t db, int sd){
  asm volatile("{ .reg .pred p; setp.ne.b32 p, %29, 0; wgmma.mma_async.sync.aligned.m64n48k16.f32.bf16.bf16 {%0,%1,%2,%3,%4,%5,%6,%7,%8,%9,%10,%11,%12,%13,%14,%15,%16,%17,%18,%19,%20,%21,%22,%23}, {%24,%25,%26,%27}, %28, p, 1, 1, %30; }"
   : "+f"(d[0]),"+f"(d[1]),"+f"(d[2]),"+f"(d[3]),"+f"(d[4]),"+f"(d[5]),"+f"(d[6]),"+f"(d[7]),"+f"(d[8]),"+f"(d[9]),"+f"(d[10]),"+f"(d[11]),"+f"(d[12]),"+f"(d[13]),"+f"(d[14]),"+f"(d[15]),"+f"(d[16]),"+f"(d[17]),"+f"(d[18]),"+f"(d[19]),"+f"(d[20]),"+f"(d[21]),"+f"(d[22]),"+f"(d[23]) : "r"(a0),"r"(a1),"r"(a2),"r"(a3), "l"(db), "r"(sd), "n"(TB));
}
template<int TB> __device__ __forceinline__ void wgmma_rs_n56(float* d, uint32_t a0, uint32_t a1, uint32_t a2, uint32_t a3, uint64_t db, int sd){
  asm volatile("{ .reg .pred p; setp.ne.b32 p, %33, 0; wgmma.mma_async.sync.aligned.m64n56k16.f32.bf16.bf16 {%0,%1,%2,%3,%4,%5,%6,%7,%8,%9,%10,%11,%12,%13,%14,%15,%16,%17,%18,%19,%20,%21,%22,%23,%24,%25,%26,%27}, {%28,%29,%30,%31}, %32, p, 1, 1, %34; }"
   : "+f"(d[0]),"+f"(d[1]),"+f"(d[2]),"+f"(d[3]),"+f"(d[4]),"+f"(d[5]),"+f"(d[6]),"+f"(d[7]),"+f"(d[8]),"+f"(d[9]),"+f"(d[10]),"+f"(d[11]),"+f"(d[12]),"+f"(d[13]),"+f"(d[14]),"+f"(d[15]),"+f"(d[16]),"+f"(d[17]),"+f"(d[18]),"+f"(d[19]),"+f"(d[20]),"+f"(d[21]),"+f"(d[22]),"+f"(d[23]),"+f"(d[24]),"+f"(d[25]),"+f"(d[26]),"+f"(d[27]) : "r"(a0),"r"(a1),"r"(a2),"r"(a3), "l"(db), "r"(sd), "n"(TB));
}
template<int TB> __device__ __forceinline__ void wgmma_rs_n64(float* d, uint32_t a0, uint32_t a1, uint32_t a2, uint32_t a3, uint64_t db, int sd){
  asm volatile("{ .reg .pred p; setp.ne.b32 p, %37, 0; wgmma.mma_async.sync.aligned.m64n64k16.f32.bf16.bf16 {%0,%1,%2,%3,%4,%5,%6,%7,%8,%9,%10,%11,%12,%13,%14,%15,%16,%17,%18,%19,%20,%21,%22,%23,%24,%25,%26,%27,%28,%29,%30,%31}, {%32,%33,%34,%35}, %36, p, 1, 1, %38; }"
   : "+f"(d[0]),"+f"(d[1]),"+f"(d[2]),"+f"(d[3]),"+f"(d[4]),"+f"(d[5]),"+f"(d[6]),"+f"(d[7]),"+f"(d[8]),"+f"(d[9]),"+f"(d[10]),"+f"(d[11]),"+f"(d[12]),"+f"(d[13]),"+f"(d[14]),"+f"(d[15]),"+f"(d[16]),"+f"(d[17]),"+f"(d[18]),"+f"(d[19]),"+f"(d[20]),"+f"(d[21]),"+f"(d[22]),"+f"(d[23]),"+f"(d[24]),"+f"(d[25]),"+f"(d[26]),"+f"(d[27]),"+f"(d[28]),"+f"(d[29]),"+f"(d[30]),"+f"(d[31]) : "r"(a0),"r"(a1),"r"(a2),"r"(a3), "l"(db), "r"(sd), "n"(TB));
}
template<int N,int TA,int TB> __device__ __forceinline__ void wgmma_ss(float* d, uint64_t da, uint64_t db, int sd){
  if constexpr(N==176) wgmma_ss_n176<TA,TB>(d,da,db,sd);
}
template<int N,int TB> __device__ __forceinline__ void wgmma_rs(float* d, uint32_t a0,uint32_t a1,uint32_t a2,uint32_t a3, uint64_t db, int sd){
  if constexpr(N==8) wgmma_rs_n8<TB>(d,a0,a1,a2,a3,db,sd);
  if constexpr(N==16) wgmma_rs_n16<TB>(d,a0,a1,a2,a3,db,sd);
  if constexpr(N==24) wgmma_rs_n24<TB>(d,a0,a1,a2,a3,db,sd);
  if constexpr(N==32) wgmma_rs_n32<TB>(d,a0,a1,a2,a3,db,sd);
  if constexpr(N==40) wgmma_rs_n40<TB>(d,a0,a1,a2,a3,db,sd);
  if constexpr(N==48) wgmma_rs_n48<TB>(d,a0,a1,a2,a3,db,sd);
  if constexpr(N==56) wgmma_rs_n56<TB>(d,a0,a1,a2,a3,db,sd);
  if constexpr(N==64) wgmma_rs_n64<TB>(d,a0,a1,a2,a3,db,sd);
}

typedef __nv_bfloat16 bf16;
constexpr int S_ = 2048, D_ = 512, F_ = 1376, FS = 176;

__device__ __forceinline__ uint32_t smem_u32(const void* p){ return (uint32_t)__cvta_generic_to_shared(p); }
__device__ __forceinline__ void mbar_init(uint32_t bar, uint32_t cnt){ asm volatile("mbarrier.init.shared::cta.b64 [%0], %1;"::"r"(bar),"r"(cnt):"memory"); }
__device__ __forceinline__ void mbar_expect_tx(uint32_t bar, uint32_t bytes){ asm volatile("mbarrier.arrive.expect_tx.shared::cta.b64 _, [%0], %1;"::"r"(bar),"r"(bytes):"memory"); }
__device__ __forceinline__ void mbar_arrive(uint32_t bar){ asm volatile("mbarrier.arrive.shared::cta.b64 _, [%0];"::"r"(bar):"memory"); }
__device__ __forceinline__ void mbar_arrive_n(uint32_t bar, uint32_t n){ asm volatile("mbarrier.arrive.shared::cta.b64 _, [%0], %1;"::"r"(bar),"r"(n):"memory"); }
__device__ __forceinline__ void mbar_arrive_cl(uint32_t cbar){ asm volatile("mbarrier.arrive.shared::cluster.b64 _, [%0];"::"r"(cbar):"memory"); }
__device__ __forceinline__ uint32_t mapa(uint32_t a, uint32_t cta){ uint32_t r; asm volatile("mapa.shared::cluster.u32 %0, %1, %2;":"=r"(r):"r"(a),"r"(cta)); return r; }
__device__ __forceinline__ void mbar_wait(uint32_t bar, uint32_t ph){
  asm volatile("{ .reg .pred p; .reg .u32 c; mov.u32 c, 0;\n"
               "WL: mbarrier.try_wait.parity.shared::cta.b64 p, [%0], %1; @p bra WD; add.u32 c,c,1; setp.lt.u32 p, c, 1000000; @p bra WL; trap;\n"
               "WD: }"::"r"(bar),"r"(ph):"memory"); }
__device__ __forceinline__ uint32_t mbar_test(uint32_t bar, uint32_t ph){ uint32_t ok; asm volatile("{ .reg .pred p; mbarrier.test_wait.parity.shared::cta.b64 p, [%1], %2; selp.u32 %0,1,0,p; }":"=r"(ok):"r"(bar),"r"(ph):"memory"); return ok; }
__device__ __forceinline__ void spin_guard(int n){ asm volatile("{ .reg .pred p; setp.gt.s32 p, %0, 2000000; @p trap; }"::"r"(n)); }
__device__ __forceinline__ bool elect_one(){ uint32_t p; asm volatile("{ .reg .pred P; elect.sync _|P, 0xffffffff; selp.u32 %0,1,0,P; }":"=r"(p)); return p; }
__device__ __forceinline__ void tma2d(uint32_t dst, const CUtensorMap* m, int c0, int c1, uint32_t bar){
  asm volatile("cp.async.bulk.tensor.2d.shared::cluster.global.mbarrier::complete_tx::bytes [%0], [%1, {%3, %4}], [%2];"::"r"(dst),"l"(m),"r"(bar),"r"(c0),"r"(c1):"memory"); }
__device__ __forceinline__ void tma2d_mc(uint32_t dst, const CUtensorMap* m, int c0, int c1, uint32_t bar){
  asm volatile("cp.async.bulk.tensor.2d.shared::cluster.global.mbarrier::complete_tx::bytes.multicast::cluster [%0], [%1, {%3, %4}], [%2], %5;"::"r"(dst),"l"(m),"r"(bar),"r"(c0),"r"(c1),"h"((uint16_t)3):"memory"); }
__device__ __forceinline__ void wg_fence(){ asm volatile("wgmma.fence.sync.aligned;":::"memory"); }
__device__ __forceinline__ void wg_commit(){ asm volatile("wgmma.commit_group.sync.aligned;":::"memory"); }
template<int N> __device__ __forceinline__ void wg_wait(){ asm volatile("wgmma.wait_group.sync.aligned %0;"::"n"(N):"memory"); }
__device__ __forceinline__ uint64_t make_desc(uint32_t addr, uint32_t lbo, uint32_t sbo, uint32_t sw){ return (uint64_t)((addr&0x3FFFF)>>4) | ((uint64_t)((lbo&0x3FFFF)>>4)<<16) | ((uint64_t)((sbo&0x3FFFF)>>4)<<32) | ((uint64_t)sw<<62); }
__device__ __forceinline__ void ldsm4t(uint32_t a, uint32_t& r0, uint32_t& r1, uint32_t& r2, uint32_t& r3){ asm volatile("ldmatrix.sync.aligned.m8n8.x4.trans.shared.b16 {%0,%1,%2,%3}, [%4];":"=r"(r0),"=r"(r1),"=r"(r2),"=r"(r3):"r"(a):"memory"); }
__device__ __forceinline__ uint32_t pack_bf16(float lo, float hi){ uint32_t r; asm("cvt.rn.bf16x2.f32 %0, %1, %2;":"=r"(r):"f"(hi),"f"(lo)); return r; }
__device__ __forceinline__ float bf_lo(uint32_t v){ return __uint_as_float(v<<16); }
__device__ __forceinline__ float bf_hi(uint32_t v){ return __uint_as_float(v&0xffff0000u); }
__device__ __forceinline__ float rbf(float x){ return __bfloat162float(__float2bfloat16(x)); }
__device__ __forceinline__ uint32_t hadd2_bf16(uint32_t a, uint32_t b){ uint32_t r; asm("add.rn.bf16x2 %0, %1, %2;":"=r"(r):"r"(a),"r"(b)); return r; }
__device__ __forceinline__ float tanh_fast(float x){ float r; asm("tanh.approx.f32 %0, %1;":"=f"(r):"f"(x)); return r; }

__device__ __forceinline__ void st_rlx128(void* p, uint32_t a, uint32_t b, uint32_t c, uint32_t d){
  asm volatile("{ .reg .b64 l,h; .reg .b128 v; mov.b64 l,{%1,%2}; mov.b64 h,{%3,%4}; mov.b128 v,{l,h}; st.relaxed.gpu.global.b128 [%0], v; }"::"l"(p),"r"(a),"r"(b),"r"(c),"r"(d):"memory"); }
__device__ __forceinline__ void ld_rlx128(const void* p, uint4& v){
  asm volatile("{ .reg .b64 l,h; .reg .b128 v; ld.relaxed.gpu.global.b128 v, [%4]; mov.b128 {l,h}, v; mov.b64 {%0,%1}, l; mov.b64 {%2,%3}, h; }":"=r"(v.x),"=r"(v.y),"=r"(v.z),"=r"(v.w):"l"(p):"memory"); }
__device__ __forceinline__ void st_async128(uint32_t dst, uint32_t a, uint32_t b, uint32_t c, uint32_t d, uint32_t cbar){
  asm volatile("st.async.weak.shared::cluster.mbarrier::complete_tx::bytes.v4.b32 [%0], {%1,%2,%3,%4}, [%5];"::"r"(dst),"r"(a),"r"(b),"r"(c),"r"(d),"r"(cbar)); }
__device__ __forceinline__ void bulk_g2s(uint32_t dst, const void* src, uint32_t bytes, uint32_t bar){
  asm volatile("cp.async.bulk.shared::cluster.global.mbarrier::complete_tx::bytes [%0], [%1], %2, [%3];"::"r"(dst),"l"(src),"r"(bytes),"r"(bar):"memory"); }
__device__ __forceinline__ void lds128(uint32_t a, uint32_t& x, uint32_t& y, uint32_t& z, uint32_t& w){ asm volatile("ld.shared.v4.u32 {%0,%1,%2,%3}, [%4];":"=r"(x),"=r"(y),"=r"(z),"=r"(w):"r"(a):"memory"); }
__device__ __forceinline__ void tma4d_red_add(const CUtensorMap* m, int c0, int c1, int c2, int c3, uint32_t src){
  asm volatile("cp.reduce.async.bulk.tensor.4d.global.shared::cta.add.tile.bulk_group [%0, {%1, %2, %3, %4}], [%5];"::"l"(m),"r"(c0),"r"(c1),"r"(c2),"r"(c3),"r"(src):"memory"); }
__device__ __forceinline__ void stsm4_nm(uint32_t a, uint32_t r0, uint32_t r1, uint32_t r2, uint32_t r3){ asm volatile("stmatrix.sync.aligned.m8n8.x4.shared.b16 [%0], {%1,%2,%3,%4};"::"r"(a),"r"(r0),"r"(r1),"r"(r2),"r"(r3)); }
__device__ __forceinline__ void tma3d(uint32_t dst, const CUtensorMap* m, int c0, int c1, int c2, uint32_t bar){
  asm volatile("cp.async.bulk.tensor.3d.shared::cluster.global.mbarrier::complete_tx::bytes [%0], [%1, {%3, %4, %5}], [%2];"::"r"(dst),"l"(m),"r"(bar),"r"(c0),"r"(c1),"r"(c2):"memory"); }
__device__ __forceinline__ uint32_t lds32(uint32_t a){ uint32_t v; asm volatile("ld.shared.u32 %0, [%1];":"=r"(v):"r"(a)); return v; }
__device__ __forceinline__ void sts128(uint32_t a, uint32_t x, uint32_t y, uint32_t z, uint32_t w){ asm volatile("st.shared.v4.u32 [%0], {%1,%2,%3,%4};"::"r"(a),"r"(x),"r"(y),"r"(z),"r"(w):"memory"); }
__device__ __forceinline__ uint4 ldg_nc128(const void* p){ uint4 v; asm volatile("ld.global.nc.L1::no_allocate.v4.u32 {%0,%1,%2,%3}, [%4];":"=r"(v.x),"=r"(v.y),"=r"(v.z),"=r"(v.w):"l"(p)); return v; }
__device__ __forceinline__ uint32_t hmul2_bf16(uint32_t a, uint32_t b){ uint32_t r; asm("mul.rn.bf16x2 %0, %1, %2;":"=r"(r):"r"(a),"r"(b)); return r; }
__device__ __forceinline__ uint32_t hfma2_bf16(uint32_t a, uint32_t b, uint32_t c){ uint32_t r; asm("fma.rn.bf16x2 %0, %1, %2, %3;":"=r"(r):"r"(a),"r"(b),"r"(c)); return r; }
__device__ __forceinline__ uint32_t hsub2_bf16(uint32_t a, uint32_t b){ uint32_t r; asm("sub.rn.bf16x2 %0, %1, %2;":"=r"(r):"r"(a),"r"(b)); return r; }
__device__ __forceinline__ void signal_add(unsigned* p){ asm volatile("fence.acq_rel.gpu;":::"memory"); asm volatile("red.relaxed.gpu.global.add.u32 [%0], 1;"::"l"(p):"memory"); }
__device__ __forceinline__ void lds128_nm(uint32_t a, uint32_t& x, uint32_t& y, uint32_t& z, uint32_t& w){ asm volatile("ld.shared.v4.u32 {%0,%1,%2,%3}, [%4];":"=r"(x),"=r"(y),"=r"(z),"=r"(w):"r"(a)); }
__device__ __forceinline__ float ln_rstd(float var){
  float sq, r; asm("sqrt.approx.f32 %0, %1;":"=f"(sq):"f"(rbf(rbf(var)+1e-5f))); asm("rcp.approx.f32 %0, %1;":"=f"(r):"f"(rbf(sq))); return r; }
__device__ __forceinline__ float4 gather_sum(const uint4* src, int n, int stride, uint32_t par){
  float4 c=make_float4(0.f,0.f,0.f,0.f);
  #pragma unroll 1
  for(int kb=0;kb<n;kb+=4){
    uint4 v[4]; int it=0;
    do{
      #pragma unroll
      for(int u=0;u<4;u++) ld_rlx128(src+u*stride, v[u]);
      spin_guard(++it);
    }while(((v[0].x^par)|(v[1].x^par)|(v[2].x^par)|(v[3].x^par))&1);
    #pragma unroll
    for(int u=0;u<4;u++){ c.x+=__uint_as_float(v[u].x); c.y+=__uint_as_float(v[u].y); c.z+=__uint_as_float(v[u].z); c.w+=__uint_as_float(v[u].w); }
    src+=4*stride;
  }
  return c;
}
__host__ __device__ __forceinline__ int pos2row(int pos){
  const int P = 1 - (pos >> 10), thr = (pos & 1023) >> 3, k = (pos>>2)&1, h = (pos>>1)&1, e = pos&1;
  const int w = thr >> 5, tp = (thr >> 3)&3, j = (thr >> 1)&3, p = thr & 1;
  return 16*(127 - (64*P + 16*j + 8*k + 2*tp + e)) + 8*h + 2*w + p;
}

__device__ __align__(1024) bf16 g_hT[D_*S_];
__device__ __align__(1024) uint4 g_xa[128*128*8];
__device__ __align__(1024) uint4 g_qs[128*8];
__device__ uint4 g_stat[16*2*8*32];
__device__ uint4 g_csp[8*16*88];
__device__ uint4 g_cs2[8*96];
__device__ unsigned g_cnt[4*32];
#define STAMP(i)

#define QDELAY 1500
#define KV0 3
#define XAFTER 5
#define XPOS 3
#define ZKV 3
#define WSTART 5
#define W9 2
#define PACE 3
#define CSLEEP 600
#define SKW 2
#define STX0 2
#define STX1 2
#define CSUN 4
#define HF 3
#define NIN 7
constexpr int CSU = CSUN;
constexpr uint32_t G2_CH = 0x33221010u, G2_PEER = 0xAC;
constexpr int NS = 6, WSLOT = 24576, NX = 4, XSLOT = 8192;
constexpr int OFF_RES0 = 0, OFF_X = 8192, OFF_RES1 = 73728, OFF_W = 81920;
constexpr int OFF_CS = OFF_W + NS*WSLOT, OFF_ROW = OFF_CS + 2*FS*4, OFF_BAR = OFF_ROW + 1024;
constexpr int TBL = 8320, UPL = 2112, UCH = 2*UPL, QP = 1088, KVCH = 4224;
constexpr int OFF_TBL = 32768, OFF_U = OFF_TBL + 4*TBL, OFF_XAL = 82944, OFF_XAE = OFF_W + 2*WSLOT;
constexpr int OFF_IMG = 0, OFF_X8 = OFF_XAL + 16384, OFF_ZB = OFF_W + WSLOT - 2048, EXB = 32*144;
#define KVOFF(T) (OFF_W + 3*WSLOT + (T)*KVCH - ((T)>>2)*(2*WSLOT+4*KVCH))
constexpr int OFF_KV = OFF_W + 3*WSLOT, OFF_Q = OFF_W + 4*WSLOT;
static_assert(OFF_X8 + EXB <= OFF_ZB && OFF_U + 4*UCH <= OFF_XAL && OFF_XAL + 16384 <= OFF_W + WSLOT, "overlay");
constexpr int B_WFULL = 0, B_WEMPTY = B_WFULL+NS, B_XFULL = B_WEMPTY+NS, B_XEMPTY = B_XFULL+2*NX, B_PRDY = B_XEMPTY+2*NX, B_AFULL = B_PRDY+2,
              B_ONE = B_AFULL+2, B_FB = B_ONE, B_INIT = B_FB+2, B_XA = B_INIT+2, B_PAR = B_XA+2, B_TD = B_PAR+2, B_KV = B_TD+1, B_U = B_KV+8, B_HD = B_U+8, B_Q = B_HD+2, B_QD = B_Q+8, B_SC = B_QD+1, B_X03 = B_SC+1, B_RT = B_X03+1, NBAR = B_RT+2;
constexpr int OFF_MISC = (OFF_BAR + NBAR*8 + 15)&~15;
constexpr int SMEM_BYTES = OFF_MISC + 16;
static_assert(SMEM_BYTES<=232448,"smem");

struct Maps { CUtensorMap k, v, xa, w64, w48, wd, ht, out, out8; int upfirst; };

__device__ __forceinline__ void load_w_stage(const Maps& maps, uint32_t dst, int col, int k0, uint32_t fb){
  asm volatile("cp.async.bulk.tensor.4d.shared::cluster.global.mbarrier::complete_tx::bytes [%0], [%1, {%3, %4, %5, %5}], [%2];"::"r"(dst),"l"(&maps.w64),"r"(fb),"r"(col),"r"(k0),"r"(0):"memory");
  tma3d(dst+16384, &maps.w48, col+128, k0, 0, fb);
}

template<int N> __device__ __forceinline__ void conv_mma(float* acc, const uint32_t* R, uint64_t db){
  wgmma_rs<N,0>(acc, R[0],R[1],R[2],R[3], db,   1);
  wgmma_rs<N,0>(acc, R[4],R[5],R[6],R[7], db+1, 1);
}
__device__ __forceinline__ void conv_lda(uint32_t* R, const uint32_t* tb, int off){
  R[0]=lds32(tb[0]+off); R[1]=lds32(tb[1]+off); R[3]=lds32(tb[2]+off); R[5]=lds32(tb[3]+off); R[7]=lds32(tb[4]+off);
}
__device__ __forceinline__ void conv_dup(uint32_t* R){
  asm volatile("mov.b32 %0, %1;":"=r"(R[2]):"r"(R[1])); asm volatile("mov.b32 %0, %1;":"=r"(R[4]):"r"(R[3])); asm volatile("mov.b32 %0, %1;":"=r"(R[6]):"r"(R[5]));
}
__device__ __forceinline__ void zero4(float* a){
  #pragma unroll
  for(int i=0;i<4;i+=2) asm volatile("mov.b64 {%0,%1}, 0;":"=f"(a[i]),"=f"(a[i+1]));
}
__device__ __forceinline__ uint32_t tid_now(){ uint32_t t; asm volatile("mov.u32 %0, %%tid.x;":"=r"(t)); return t; }
__device__ __forceinline__ void load_xs(uint4* x, uint4* st, uint32_t sb, int warp, int lane){
  const uint32_t tw = (warp&3)*32+lane, pc = ((warp>>2)*2)^(tw&7);
  #pragma unroll
  for(int i=0;i<4;i++) lds128(sb+OFF_XAL+tw*128+((pc^(i&1)^((i>>1)*4))<<4), x[i].x,x[i].y,x[i].z,x[i].w);
  #pragma unroll
  for(int i=0;i<8;i++) lds128(sb+OFF_XAE+tw*128+((i^(tw&7))<<4), st[i].x,st[i].y,st[i].z,st[i].w);
}
__device__ __forceinline__ void check_xs(uint4* x, uint4* st, uint32_t ep, uint32_t sb, int warp){
  for(int n=0;n<2000000;n++){
    uint32_t bad=0;
    #pragma unroll
    for(int i=0;i<8;i++) bad|=st[i].w^ep;
    if(!bad && x[0].x && x[1].x && x[2].x && x[3].x) break;
    const uint32_t t2=tid_now()&127, pc = ((warp>>2)*2)^(t2&7);
    #pragma unroll
    for(int i=0;i<4;i++) ld_rlx128(&g_xa[blockIdx.x*1024+t2*8+(pc^(i&1)^((i>>1)*4))], x[i]);
    #pragma unroll
    for(int i=0;i<8;i++) ld_rlx128(&g_qs[t2*8+(i^(t2&7))], st[i]);
  }
  __syncwarp();
}
__device__ __forceinline__ void ln_x(uint4* x, const uint4* st, uint4* a){
#define LNA(X,S) ({ const uint32_t d_=hsub2_bf16(X,S.x); hfma2_bf16(d_,S.y,hmul2_bf16(d_,S.z)); })
  #pragma unroll
  for(int i=0;i<2;i++){
    x[i].x=~x[i].x;
    a[i].x=LNA(x[i].x,st[0]); a[i].y=LNA(x[i].y,st[1]); a[i].z=LNA(x[i].z,st[2]); a[i].w=LNA(x[i].w,st[3]);
  }
}
template<int PART> __device__ __forceinline__ uint32_t ex_buf(uint32_t sb, int warp){
  return sb + (PART? (warp<7? OFF_IMG+warp*EXB : OFF_X8) : ((warp&3)<3? OFF_TBL+(warp>>2)*2*TBL+(warp&3)*EXB : OFF_XAL+(warp>>2)*EXB)); }
template<int PART> __device__ __forceinline__ void conv_put(const float* a0, const float* a1, uint4& e0, uint32_t sb, int warp, int lane){
  const uint32_t ad = ex_buf<PART>(sb,warp) + ((lane&24)|((lane&3)<<1)|((lane>>2)&1))*144;
  if(PART) sts128(ad+128, 0,0,0,0); else sts128(ad+128, e0.x,e0.y,e0.z,e0.w);
  #pragma unroll
  for(int ii=0;ii<8;ii++){
    const uint32_t w0=pack_bf16(a0[4*ii],a0[4*ii+1]), w1=pack_bf16(a0[4*ii+2],a0[4*ii+3]), w2=pack_bf16(a1[4*ii],a1[4*ii+1]), w3=pack_bf16(a1[4*ii+2],a1[4*ii+3]);
    sts128(ad+ii*16, w0,w1,w2,w3);
    if(PART && ii==0) e0=make_uint4(w0,w1,w2,w3);
  }
  __syncwarp();
}
template<int PART> __device__ __forceinline__ void conv_get(const uint4* x, const uint4* a, uint32_t sb, int warp, int lane){
  const int cb = blockIdx.x, chl = (warp>>2)*2;
  const uint32_t tw = (warp&3)*32+lane;
  const uint32_t eb = ex_buf<PART>(sb,warp) + (lane&1)*144 + (lane&6)*16 + (lane>>3)*288;
  uint4 d[4][2];
  #pragma unroll
  for(int c=0;c<4;c++){
    const uint32_t ad = eb + c*(8*144+288) - (((lane>>3)+c>3)? 4*288-16 : 0);
    lds128(ad, d[c][0].x,d[c][0].y,d[c][0].z,d[c][0].w);
    lds128(ad+16, d[c][1].x,d[c][1].y,d[c][1].z,d[c][1].w);
  }
#define SUM4(K,F) hadd2_bf16(hadd2_bf16(d[0][K].F,d[1][K].F),hadd2_bf16(d[2][K].F,d[3][K].F))
  uint4 o0, o1;
  o0.x=hadd2_bf16(x[0].x,hmul2_bf16(a[0].x,SUM4(0,x))); o0.y=hadd2_bf16(x[0].y,hmul2_bf16(a[0].y,SUM4(0,y)));
  o0.z=hadd2_bf16(x[0].z,hmul2_bf16(a[0].z,SUM4(1,x))); o0.w=hadd2_bf16(x[0].w,hmul2_bf16(a[0].w,SUM4(1,y)));
  o1.x=hadd2_bf16(x[1].x,hmul2_bf16(a[1].x,SUM4(0,z))); o1.y=hadd2_bf16(x[1].y,hmul2_bf16(a[1].y,SUM4(0,w)));
  o1.z=hadd2_bf16(x[1].z,hmul2_bf16(a[1].z,SUM4(1,z))); o1.w=hadd2_bf16(x[1].w,hmul2_bf16(a[1].w,SUM4(1,w)));
  uint4* dst = (uint4*)(g_hT + (cb*4+chl)*2048 + (1-PART)*1024) + tw;
  const uint32_t par = lds32(sb+OFF_MISC)&1;
  o0.x=(o0.x&~1u)|par; o1.x=(o1.x&~1u)|par;
  dst[0]=o0; dst[256]=o1;
}

__device__ __forceinline__ bool x_bad(uint32_t sb, int wg, int wq, int lane){
  const uint32_t xbase = sb+OFF_X+wg*NX*XSLOT, rbase = sb+(wg? OFF_RES1:OFF_RES0), par = lds32(sb+OFF_MISC), co = lane*128+(((2*wq)^(lane&7))<<4);
  uint32_t bad=0;
  #pragma unroll
  for(int i=0;i<8;i++) bad |= lds32((i<6? xbase+i*4096 : rbase+(i-6)*4096)+co)^par;
  return __any_sync(~0u, bad&1);
}
__device__ __forceinline__ void first_x(const Maps& maps, uint32_t sb, int w){
  const int b = blockIdx.x, rank = b&1, rt = b>>3;
  const uint32_t bar = sb+OFF_BAR, xf = bar+8*(B_XFULL+w*NX), xd = sb+OFF_X+w*NX*XSLOT+rank*4096, rb = sb+(w? OFF_RES1:OFF_RES0);
  const int c0 = w*1024+rt*64, k0 = (rt>>1)+w*(SKW/2), cr = rank*256+((b>>1)&3)*64;
  mbar_expect_tx(xf, 4*XSLOT); mbar_arrive(xf+8); mbar_arrive(xf+16);
  const unsigned tgt = lds32(sb+OFF_MISC)*128;
  mbar_wait(bar+8*(B_HD+w), 0);
  {
    unsigned v; int n=0;
    asm volatile("red.relaxed.gpu.global.add.u32 [%0], 1;"::"l"(&g_cnt[w? 0:96]):"memory");
    do{ asm volatile("ld.relaxed.gpu.global.u32 %0, [%1];":"=r"(v):"l"(&g_cnt[w? 0:96]):"memory"); }while((int)(v-tgt)<0 && ++n<2000000);
  }
  tma2d_mc(xd,         &maps.ht, c0, (k0&7)*64+rank*32,     xf);
  tma2d_mc(xd+XSLOT,   &maps.ht, c0, ((k0+1)&7)*64+rank*32, xf);
  tma2d_mc(xd+2*XSLOT, &maps.ht, c0, ((k0+2)&7)*64+rank*32, xf);
  tma2d(rb,      &maps.ht, c0, cr,    xf);
  tma2d(rb+4096, &maps.ht, c0, cr+32, xf);
}

__global__ void __cluster_dims__(2,1,1) __launch_bounds__(384,1)
fused_kernel(const __grid_constant__ Maps maps, const bf16* __restrict__ q, const bf16* __restrict__ shk, const bf16* __restrict__ ssmk,
             const bf16* __restrict__ ssmD, const bf16* __restrict__ wdn, bf16* __restrict__ out){
  extern __shared__ __align__(1024) uint8_t smem_raw[];
  if(threadIdx.x<32){ if(elect_one()){ asm volatile("cp.async.bulk.prefetch.L2.global [%0], 16384;"::"l"(q+blockIdx.x*8192)); } }
  unsigned c_begin; asm volatile("mov.u32 %0, %%clock;":"=r"(c_begin));
  const uint32_t sb = smem_u32(smem_raw);
  const int tid = threadIdx.x, lane = tid&31;
  const int warp = __shfl_sync(0xffffffffu, tid>>5, 0);
  const int wg = warp>>2;
  const int b = blockIdx.x, rank = b&1;
  const int f = b&7, rt = b>>3, fp = f>>1;
  const uint32_t bar = sb+OFF_BAR;

  if(wg==2){
    asm volatile("setmaxnreg.dec.sync.aligned.u32 56;");
    STAMP(58);
    const int cg = b>>1;
    const int cb = cg*2+rank;
    unsigned epoch = 0; uint4 shw = make_uint4(0,0,0,0); uint2 dd = make_uint2(0,0);
    if(warp!=9){
      asm volatile("ld.relaxed.gpu.global.u32 %0, [%1];":"=r"(epoch):"l"(&g_cnt[(lane&3)*32]));
      shw = ldg_nc128(shk + (cg*8+(lane&3)*2)*4);
      asm volatile("ld.global.nc.v2.u32 {%0,%1}, [%2];":"=r"(dd.x),"=r"(dd.y):"l"(ssmD + cb*4));
    }
    auto ldkv=[&](int i){
      const uint32_t fb=bar+8*(B_KV+i);
      mbar_expect_tx(fb, 2176+2048);
      tma3d(sb+KVOFF(i),      &maps.k, cg*8, i*32+rank*16-1, 0, fb);
      tma3d(sb+KVOFF(i)+2176, &maps.v, cg*8, i*32+rank*16,   0, fb);
    };
    if(warp==9){
      if(lane<3) asm volatile("prefetch.tensormap [%0];"::"l"(&maps.k+lane):"memory");
    }
    STAMP(51+warp);
    asm volatile("bar.sync 0;":::"memory");
    asm volatile("barrier.cluster.arrive.relaxed.aligned;":::"memory");
    if(warp==9){
      { unsigned c1; do{ asm volatile("mov.u32 %0, %%clock;":"=r"(c1)); }while(c1-c_begin<QDELAY); }
      if(elect_one()){
        #pragma unroll
        for(int i=0;i<KV0;i++) ldkv(i);
      }
      __syncwarp();
      mbar_wait(bar+8*B_QD, 0);
      STAMP(79);
      if(elect_one()){
        asm volatile("cp.async.bulk.tensor.2d.global.shared::cta.bulk_group [%0, {%1, %2}], [%3];"::"l"(&maps.xa),"r"(b*64),"r"(0),"r"(sb+OFF_IMG):"memory");
        asm volatile("cp.async.bulk.commit_group;":::"memory");
        #pragma unroll 1
        for(int i=KV0;i<8;i++){
          ldkv(i);
          if(i==XAFTER){
            asm volatile("cp.async.bulk.wait_group.read 0;":::"memory");
            mbar_wait(bar+8*(B_KV+XPOS), 0);
            mbar_expect_tx(bar+8*B_XA, 32768); bulk_g2s(sb+OFF_XAL, &g_xa[cb*1024], 16384, bar+8*B_XA); bulk_g2s(sb+OFF_XAE, g_qs, 16384, bar+8*B_XA);
            STAMP(66);
          }
        }
        mbar_wait(bar+8*B_WEMPTY, 0);
        mbar_wait(bar+8*(B_KV+ZKV), 0);
        #pragma unroll
        for(int i=0;i<8;i++) asm volatile("cp.async.bulk.global.shared::cta.bulk_group [%0], [%1], 2048;"::"l"(out+b*8192+i*1024),"r"(sb+OFF_ZB):"memory");
        asm volatile("cp.async.bulk.commit_group;":::"memory");
        mbar_wait(bar+8*(B_KV+WSTART), 0);
        #pragma unroll 1
        for(int it=0;it<W9;it++){
          mbar_wait(bar+8*(B_WEMPTY+it), 0);
          if(it>=PACE) mbar_wait(bar+8*(B_WFULL+it-PACE), 0);
          mbar_expect_tx(bar+8*(B_WFULL+it), 22528);
          load_w_stage(maps, sb+OFF_W+(5-it)*WSLOT, f*FS, ((it+(rt&14))&15)*32, bar+8*(B_WFULL+it));
          STAMP(24+it);
        }
        asm volatile("cp.async.bulk.wait_group 0;":::"memory");
        asm volatile("fence.proxy.async.global;":::"memory");
        mbar_arrive(bar+8*(B_HD+1));
        STAMP(30);
      }
      __syncwarp();
    }
    asm volatile("":"+r"(epoch));
    epoch = (epoch>>7)+1;
    if(warp==11){
      if(lane==0) sts128(sb+OFF_MISC, epoch, dd.x, dd.y, 0);
      __syncwarp();
      if(lane==0) mbar_arrive(bar+8*B_SC);
    }
    if(warp==8 && lane<6) asm volatile("prefetch.tensormap [%0];"::"l"(&maps.w64+lane):"memory");
    if(warp==9){ mbar_wait(bar+8*B_SC, 0); epoch = lds32(sb+OFF_MISC); }
    const uint32_t par = epoch&1;
    auto ldx=[&](int w, int it){
      const uint32_t fb = bar+8*(B_XFULL+w*NX+(it&3));
      mbar_expect_tx(fb, XSLOT);
      tma2d_mc(sb+OFF_X+(w*NX+(it&3))*XSLOT+rank*4096, &maps.ht, w*1024+rt*64, ((it+(rt>>1)+w*(SKW/2))&7)*64+rank*32, fb);
    };
    if(warp!=9){
      const int cp = lane&3;
      uint32_t sw[4];
      { const uint4 w = shw;
        sw[0]=__byte_perm(w.x,w.z,0x5410); sw[1]=__byte_perm(w.x,w.z,0x7632); sw[2]=__byte_perm(w.y,w.w,0x5410); sw[3]=__byte_perm(w.y,w.w,0x7632); }
      const uint32_t udst = mapa(sb+OFF_U+(cp&1)*2*UCH, cp>>1), ubar = mapa(bar+8*B_U, cp>>1);
      asm volatile("barrier.cluster.wait.aligned;":::"memory");
      #pragma unroll 1
      for(int tk=(warp==8? 2:warp-10); tk<16; tk+=3){
        const int T=tk>>1, gl=(tk&1)*8+(lane>>2);
        mbar_wait(bar+8*(B_KV+T), 0);
        if(!(tk&1)) STAMP(8+T);
        const uint32_t ka = sb+KVOFF(T)+gl*16+cp*4, va = ka+2176;
        uint32_t kk[11], u[8];
        #pragma unroll
        for(int r=0;r<3;r++) kk[r]=lds32(ka+(5+r)*272);
        #pragma unroll
        for(int r=0;r<8;r++){ kk[3+r]=lds32(ka+16+r*272); u[r]=lds32(va+r*256); }
        #pragma unroll
        for(int r=0;r<8;r++){
          uint32_t a=hmul2_bf16(kk[r],sw[3]); a=hadd2_bf16(a,hmul2_bf16(kk[r+1],sw[2])); a=hadd2_bf16(a,hmul2_bf16(kk[r+2],sw[1])); a=hadd2_bf16(a,hmul2_bf16(kk[r+3],sw[0]));
          u[r]=hmul2_bf16(a,u[r]);
        }
        const int R = 255-(T*32+rank*16+gl);
        const uint32_t d = udst + (R&1)*UPL + (R>>1)*16;
        st_async128(d,     __byte_perm(u[7],u[6],0x5410), __byte_perm(u[5],u[4],0x5410), __byte_perm(u[3],u[2],0x5410), __byte_perm(u[1],u[0],0x5410), ubar+8*T);
        st_async128(d+UCH, __byte_perm(u[7],u[6],0x7632), __byte_perm(u[5],u[4],0x7632), __byte_perm(u[3],u[2],0x7632), __byte_perm(u[1],u[0],0x7632), ubar+8*T);
      }
      __syncwarp();
      if(lane==0) mbar_arrive(bar+8*B_TD);
    } else {
      asm volatile("barrier.cluster.wait.aligned;":::"memory");
    }
    if(warp==8){
      if(elect_one()){
        const int col = f*FS;
        #pragma unroll
        for(int it=W9; it<NS; it++){
          mbar_wait(bar+8*(B_WEMPTY+it), 0);
          if(it==4) mbar_wait(bar+8*B_TD, 0);
          if(it==5) mbar_wait(bar+8*(B_HD+1), 0);
          if(it>=PACE) mbar_wait(bar+8*(B_WFULL+it-PACE), 0);
          mbar_expect_tx(bar+8*(B_WFULL+it), 22528);
          load_w_stage(maps, sb+OFF_W+(5-it)*WSLOT, col, ((it+(rt&14))&15)*32, bar+8*(B_WFULL+it));
          if(it<5) STAMP(24+it);
        }
        mbar_wait(bar+8*(B_INIT+1), 0);
        mbar_wait(bar+8*B_X03, 0); ldx(0,3);
        uint32_t wb = bar, dst = sb+OFF_W+5*WSLOT, ph = 1; int k0 = ((6+(rt&14))&15)*32;
        #pragma unroll 1
        for(int j=4; j<4+(10+SKW)/2; j++){
          mbar_wait(wb+8*B_WEMPTY, ph);
          mbar_expect_tx(wb, 22528);       load_w_stage(maps, dst, col, k0, wb);
          mbar_wait(wb+8*B_WEMPTY+8, ph);
          mbar_expect_tx(wb+8, 22528);     load_w_stage(maps, dst-WSLOT, col, k0+32, wb+8);
          if(j<8){ mbar_wait(bar+8*(B_XEMPTY+(j&3)), 0); ldx(0,j); }
          const int j1 = j-SKW/2;
          if(j1>=4 && j1<8){ if(j1==4) mbar_wait(bar+8*(B_FB+1), 0); mbar_wait(bar+8*(B_XEMPTY+NX+(j1&3)), 0); ldx(1,j1); }
          if(j==5) asm volatile("cp.async.bulk.prefetch.L2.global [%0], 11008;"::"l"(wdn+b*5504):"memory");
          const bool wrap = wb==bar+32;
          wb = wrap? bar : wb+16; dst = wrap? dst+4*WSLOT : dst-2*WSLOT; ph ^= wrap; k0 = (k0+64)&511;
        }
        #pragma unroll
        for(int j=0;j<8;j++){
          constexpr int I0=16+SKW;
          const int slot=(I0+j)%NS, ci=(G2_CH>>(4*j))&3, kh=((G2_PEER>>j)&1)^rank;
          mbar_wait(bar+8*(B_WEMPTY+slot), ((I0+j)/NS)&1);
          mbar_expect_tx(bar+8*(B_WFULL+slot), 22528);
          tma2d(sb+OFF_W+(5-slot)*WSLOT, &maps.wd, rank*256+((fp+ci)&3)*64, (2*fp+kh)*FS, bar+8*(B_WFULL+slot));
        }
      }
      __syncwarp();
    } else if(warp==11){
      if(elect_one()) first_x(maps, sb, 0);
      __syncwarp();
      STAMP(63);
      mbar_wait(bar+8*(B_INIT+1), 0);
      __nanosleep(CSLEEP);
      STAMP(31);
      {
        const int j = rt*6+(lane>>2);
        float4 c = make_float4(0.f,0.f,0.f,0.f);
        if(lane<24 && j<88) c = gather_sum(&g_csp[(f*16+(lane&3)*4)*88+j], 4, 88, par);
        __syncwarp();
        #pragma unroll
        for(int o=1;o<4;o<<=1){ c.x+=__shfl_xor_sync(~0u,c.x,o); c.y+=__shfl_xor_sync(~0u,c.y,o); c.z+=__shfl_xor_sync(~0u,c.z,o); c.w+=__shfl_xor_sync(~0u,c.w,o); }
        if(lane<24 && j<88 && !(lane&3)) st_rlx128(&g_cs2[f*96+j], (__float_as_uint(c.x)&~1u)|par, __float_as_uint(c.y), __float_as_uint(c.z), __float_as_uint(c.w));
      }
      STAMP(29);
      { uint4 v[3]; int n=0; const int j2 = lane<24? lane+64 : lane;
        do{ __nanosleep(CSLEEP); ld_rlx128(&g_cs2[f*96+lane], v[0]); ld_rlx128(&g_cs2[f*96+lane+32], v[1]); ld_rlx128(&g_cs2[f*96+j2], v[2]); spin_guard(++n); }while(((v[0].x^par)|(v[1].x^par)|(v[2].x^par))&1);
        *(uint4*)(smem_raw+OFF_CS+lane*16)=v[0]; *(uint4*)(smem_raw+OFF_CS+(lane+32)*16)=v[1]; *(uint4*)(smem_raw+OFF_CS+j2*16)=v[2]; }
      mbar_wait(bar+8*(B_FB+1), 0);
      __syncwarp();
      if(lane<2) mbar_arrive(bar+8*(B_PAR+lane));
      STAMP(74);
      #pragma unroll 4
      for(int i=0;i<32;i++) g_xa[cb*1024+i*32+lane]=make_uint4(0,0,0,0);
    } else {
      const int w = warp-9;
      mbar_wait(bar+8*(B_HD+w), 0);
      STAMP(67+w*3);
      if(elect_one()){
        signal_add(&g_cnt[32+32*w]); STAMP(68+w*3);
        unsigned v; int n=0; do{ asm volatile("ld.acquire.gpu.global.u32 %0, [%1];":"=r"(v):"l"(&g_cnt[32+32*w]):"memory"); spin_guard(++n); }while((int)(v-epoch*128)<0);
        STAMP(7+w*16);
        asm volatile("fence.proxy.async.global;":::"memory");
        if(w) ldx(1,3); else mbar_arrive(bar+8*B_X03);
        mbar_arrive(bar+8*(B_FB+w));
      }
      __syncwarp();
      mbar_wait(bar+8*(B_RT+w), 0);
      {
        __nanosleep(CSLEEP);
        const float4 st=gather_sum(&g_stat[((rt*2+w)*8)*32+lane], 8, 32, par);
        const float s0=st.x, q0=st.y, s1=st.z, q1=st.w;
        const float m0=s0*(1.f/512), m1=s1*(1.f/512);
        const float v0=fmaxf(q0*(1.f/512)-m0*m0,0.f), v1=fmaxf(q1*(1.f/512)-m1*m1,0.f);
        const float r0=ln_rstd(v0), r1=ln_rstd(v1);
        *(float4*)(smem_raw+OFF_ROW+w*512+lane*16)=make_float4(-rbf(m0),r0,-rbf(m1),r1);
        mbar_wait(bar+8*(B_XEMPTY+w*NX+3), 0);
        __syncwarp();
        if(lane==0) mbar_arrive(bar+8*(B_PAR+w));
        STAMP(75+w);
      }
      if(elect_one()){
        const int orow = pos2row(w*1024+rt*64+53);
        #pragma unroll
        for(int c=0;c<HF;c++){
          mbar_wait(bar+8*(B_XEMPTY+w*NX+c), 1);
          tma4d_red_add(&maps.out8, rank*256+((fp+c)&3)*64, orow&7, (orow>>3)&15, orow>>7, sb+OFF_X+(w*NX+c)*XSLOT);
        }
        asm volatile("cp.async.bulk.commit_group;":::"memory");
        asm volatile("cp.async.bulk.wait_group.read 0;":::"memory");
        STAMP(77+w);
      }
      __syncwarp();
    }
  } else {
    if(elect_one()){
      mbar_init(bar+8*(B_Q+warp),1);
      asm volatile("fence.proxy.async.shared::cta;":::"memory");
      mbar_expect_tx(bar+8*(B_Q+warp), 2048);
      const bf16* qp = q + pos2row((1-wg)*1024+b*8+(warp&3)*2)*512;
      bulk_g2s(sb+OFF_Q+2*warp*QP, qp, 1024, bar+8*(B_Q+warp)); bulk_g2s(sb+OFF_Q+(2*warp+1)*QP, qp-16*512, 1024, bar+8*(B_Q+warp));
    }
    __syncwarp();
    asm volatile("setmaxnreg.inc.sync.aligned.u32 224;");
    if(elect_one()){
      mbar_init(bar+8*(B_U+warp),1); mbar_expect_tx(bar+8*(B_U+warp), 2048);
      mbar_init(bar+8*(B_XFULL+warp),1); mbar_init(bar+8*(B_XEMPTY+warp),8);
      mbar_init(bar+8*(B_KV+warp),1);
      if(warp<NS){ mbar_init(bar+8*(B_WFULL+warp),1); mbar_init(bar+8*(B_WEMPTY+warp),8); mbar_init(bar+8*(B_ONE+warp),1); }
      else { const int i=warp-6; mbar_init(bar+8*(B_PRDY+i),4); mbar_init(bar+8*(B_RT+i),1); mbar_init(bar+8*(B_AFULL+i),1); mbar_expect_tx(bar+8*(B_AFULL+i), 22528); mbar_init(bar+8*(B_PAR+i),2); mbar_init(bar+8*(B_HD+i),8+i); if(i){ mbar_init(bar+8*B_SC,1); mbar_init(bar+8*B_X03,1); } else { mbar_init(bar+8*B_QD,8); mbar_init(bar+8*B_TD,3); } }
      asm volatile("fence.mbarrier_init.release.cluster;":::"memory");
    }
    __syncwarp();
    STAMP(56);
    const int wq = warp&3, g = lane>>2, t = lane&3;
    if(tid<8){ sts128(sb+OFF_U+tid*UPL+128*16, 0,0,0,0); }
    if(tid<128) sts128(sb+OFF_ZB+tid*16, 0,0,0,0);
    if(tid<12){ sts128(sb+OFF_TBL+(tid&3)*TBL+(tid>>2)*16, 0,0,0,0); }
    uint4 kq[4]; uint32_t kn[4];
    #pragma unroll
    for(int i=0;i<4;i++){ kq[i]=ldg_nc128(ssmk+(b*4+i)*2048+tid*8); kn[i]=0; if(lane==31 && warp<7) asm volatile("ld.global.nc.u32 %0, [%1];":"=r"(kn[i]):"l"(ssmk+(b*4+i)*2048+tid*8+8)); }
    asm volatile("bar.sync 0;":::"memory");
    asm volatile("barrier.cluster.arrive.relaxed.aligned;":::"memory");
    STAMP(57);
    #pragma unroll
    for(int i=0;i<4;i++) mbar_wait(bar+8*(B_Q+wg*4+i), 0);
    STAMP(92+wg);
    {
      const uint32_t la = sb+OFF_Q+(wg*8+2*(lane>>3)+(lane&1))*QP + ((lane&7)>>1)*16 + wq*256;
      uint4 tv[4];
      const int irow = wq*32+t*2+(g>>2);
      const uint32_t dst = sb+OFF_IMG+irow*128+(((((g&3)+4*wg)^(b&7))^(irow&7))<<4);
      #pragma unroll
      for(int i=0;i<4;i++) ldsm4t(la+i*64, tv[i].x,tv[i].y,tv[i].z,tv[i].w);
      #pragma unroll
      for(int i=0;i<4;i++) sts128(dst+i*1024, max(~tv[i].x,1u),tv[i].y,tv[i].z,tv[i].w);
      asm volatile("fence.proxy.async.shared::cta;":::"memory");
      __syncwarp();
      if(lane==0) mbar_arrive(bar+8*B_QD);
      if(wg==0) STAMP(44);
    }
    {
      uint32_t w[2][8];
      const uint32_t qa = sb+OFF_Q+(2*warp)*QP+lane*16;
      #pragma unroll
      for(int r=0;r<2;r++){ lds128_nm(qa+r*QP, w[r][0],w[r][1],w[r][2],w[r][3]); lds128_nm(qa+r*QP+512, w[r][4],w[r][5],w[r][6],w[r][7]); }
      float s[2], d[2];
      #pragma unroll
      for(int r=0;r<2;r++){
        float s0=0.f,s1=0.f,d0=0.f,d1=0.f;
        #pragma unroll
        for(int i=0;i<8;i++){ const float lo=bf_lo(w[r][i]), hi=bf_hi(w[r][i]); s0+=lo; s1+=hi; d0=fmaf(lo,lo,d0); d1=fmaf(hi,hi,d1); }
        s[r]=s0+s1; d[r]=d0+d1;
      }
      const bool u=lane&16, v=lane&8;
      const float a0=(u? s[1]:s[0])+__shfl_xor_sync(~0u,u? s[0]:s[1],16), a1=(u? d[1]:d[0])+__shfl_xor_sync(~0u,u? d[0]:d[1],16);
      float c0=(v? a1:a0)+__shfl_xor_sync(~0u,v? a0:a1,8);
      c0+=__shfl_xor_sync(~0u,c0,4); c0+=__shfl_xor_sync(~0u,c0,2); c0+=__shfl_xor_sync(~0u,c0,1);
      const float m=c0*(1.f/512), sq=__shfl_down_sync(~0u,c0,8);
      const float rs=ln_rstd(fmaxf(fmaf(-m,m,sq*(1.f/512)),0.f)), rh=rbf(rs);
      const float m1=__shfl_down_sync(~0u,m,16), rs1=__shfl_down_sync(~0u,rs,16), rh1=rbf(rs1);
      mbar_wait(bar+8*B_SC, 0);
      if(lane==0){ st_rlx128(&g_qs[b*8+(warp^(b&7))], pack_bf16(m,m1), pack_bf16(rh,rh1), pack_bf16(rs-rh,rs1-rh1), lds32(sb+OFF_MISC)); }
      __syncwarp();
      if(wg==0) STAMP(46);
    }
    mbar_wait(bar+8*B_SC, 0);
    STAMP(90+wg);
    {
      const int Q = tid+2;
      const uint32_t ta = sb+OFF_TBL+((Q*32)^(((Q>>2)&3)<<5));
      const bool sw2 = (Q>>2)&1;
      if(tid==0){
        const uint32_t d01=lds32(sb+OFF_MISC+4), d23=lds32(sb+OFF_MISC+8);
        kq[0].x=hadd2_bf16(kq[0].x,d01&0xffffu); kq[1].x=hadd2_bf16(kq[1].x,d01>>16); kq[2].x=hadd2_bf16(kq[2].x,d23&0xffffu); kq[3].x=hadd2_bf16(kq[3].x,d23>>16);
      }
      __syncwarp();
      #pragma unroll
      for(int i=0;i<4;i++){
        uint32_t nx = __shfl_down_sync(~0u, kq[i].x, 1); if(lane==31) nx = kn[i];
        const uint4 o = make_uint4(__byte_perm(kq[i].x,kq[i].y,0x5432), __byte_perm(kq[i].y,kq[i].z,0x5432), __byte_perm(kq[i].z,kq[i].w,0x5432), __byte_perm(kq[i].w,nx,0x5432));
        const uint4 f0 = sw2? o:kq[i], f1 = sw2? kq[i]:o;
        sts128(ta+i*TBL+(sw2?16:0), f0.x,f0.y,f0.z,f0.w);
        sts128(ta+i*TBL+(sw2?0:16), f1.x,f1.y,f1.z,f1.w);
        if(tid==0) sts128(sb+OFF_TBL+i*TBL+48, 0,0,0, kq[i].x<<16);
      }
      __syncwarp();
      asm volatile("bar.sync 1, 256;":::"memory");
    }
    __syncwarp();
    if(lane<3) mbar_arrive(bar+8*(B_WEMPTY+(lane==2? 4:lane)));
    STAMP(80+wg);
    STAMP(82+wg);
    asm volatile("barrier.cluster.wait.aligned;":::"memory");
    bool x_ok = false;
    {
      const int c=lane>>3, p=g&1;
      uint32_t tb[5];
      #pragma unroll
      for(int s=0;s<5;s++){ const int y=16*c+wq+t+p+4*s; const int id=8*(y>>2)+4*(1-p)+(y&3); tb[s]=sb+OFF_TBL+wg*2*TBL+((id^(((id>>5)&3)<<3))<<2); }
      uint64_t du = make_desc(sb+OFF_U+wg*2*UCH, UPL, 128, 0);
      float aE[2][32], aL[2][32];
      uint32_t R[2][4][8], oku=0; uint4 xr[4], st[8], ar[2], e0;
#define P_TY(K) ((K)>=8 ? 2 : (K)&1)
#define P_LV(K) ((K)>=8 ? (K)-8 : (K)>>1)
#define P_MA(K) ((P_TY(K)==1 ? 15 : 7) - 2*P_LV(K))
#define P_N(K,M) (P_TY(K)==2 ? 64 : P_TY(K)==1 ? 128-8*(M) : 64-8*(M))
#define P_B(K,M) (8*(M) + (P_TY(K)==0 ? 64 : 0))
#define P_LD(K,J) conv_lda(R[(K)&1][J],tb,((J)&1)*TBL+(P_MA(K)-((J)>>1))*512)
#define P_MMA(K,J) conv_mma<P_N(K,P_MA(K)-((J)>>1))>(P_TY(K)==0? aE[(J)&1]:aL[(J)&1], R[(K)&1][J], du+((J)&1)*(UCH/16)+P_B(K,P_MA(K)-((J)>>1)))
#define CONV_PREP(K) { if constexpr(P_TY(K)!=1) oku = mbar_test(bar+8*(B_U+P_LV(K)+(P_TY(K)?4:0)),0); P_LD(K,0); P_LD(K,1); P_LD(K,2); P_LD(K,3); }
#define CONV_PAIR(K) { \
        _Pragma("unroll") for(int j=0;j<4;j++) conv_dup(R[(K)&1][j]); \
        if constexpr(P_TY(K)<2){ _Pragma("unroll") for(int i=0;i<2;i++){ float* a_=(P_TY(K)==0? aE[i]:aL[i])+8*P_LV(K); zero4(a_); zero4(a_+4); } } \
        if constexpr(P_TY(K)!=1){ if(!oku) mbar_wait(bar+8*(B_U+P_LV(K)+(P_TY(K)?4:0)),0); asm volatile("fence.proxy.async.shared::cta;":::"memory"); } \
        asm volatile("" : "+l"(du)); \
        PP_SYNC(); \
        if constexpr((K)==0||(K)==6||(K)==7||(K)==11){ if(wg==0) STAMP(96+(K)); } \
        wg_fence(); \
        P_MMA(K,0); P_MMA(K,1); \
        if constexpr(P_TY(K)<2){ wg_commit(); wg_fence(); } \
        P_MMA(K,2); P_MMA(K,3); \
        wg_commit(); \
        if((K)<11 || wg==0) PP_ARRIVE(); \
        if constexpr((K)<11){ if constexpr((K)>0){ if constexpr(P_TY(K)<2) wg_wait<2>(); else wg_wait<1>(); } if constexpr((K)!=6 && (K)!=0) CONV_PREP((K)+1) } }
#define PP_SYNC() asm volatile("bar.sync %0, 256;"::"r"(2+wg):"memory")
#define PP_ARRIVE() asm volatile("bar.arrive %0, 256;"::"r"(3-wg):"memory")
      if(wg==1) PP_ARRIVE();
      CONV_PREP(0) CONV_PREP(1) CONV_PAIR(0) CONV_PAIR(1) CONV_PAIR(2) CONV_PAIR(3) CONV_PAIR(4) CONV_PAIR(5)
      mbar_wait(bar+8*B_XA,0);
      wg_wait<0>();
      load_xs(xr,st,sb,warp,lane); check_xs(xr,st,lds32(sb+OFF_MISC),sb,warp); ln_x(xr+2,st+4,ar);
      if(lane==0) mbar_arrive(bar+8*(B_WEMPTY+3));
      CONV_PAIR(6)
      if(lane==0) mbar_arrive(bar+8*(B_WEMPTY+2));
      wg_wait<0>();
      conv_put<1>(aE[0],aE[1],e0,sb,warp,lane);
      CONV_PREP(7)
      conv_get<1>(xr+2,ar,sb,warp,lane);
      __syncwarp();
      if(lane==0) mbar_arrive(bar+8*B_HD);
      STAMP(84+wg);
      CONV_PAIR(7) CONV_PAIR(8) CONV_PAIR(9) CONV_PAIR(10) CONV_PAIR(11)
      ln_x(xr,st,ar);
      if(wg==0 && mbar_test(bar+8*B_XFULL, 0)) x_ok = !x_bad(sb, 0, wq, lane);
      wg_wait<0>();
      STAMP(86+wg);
      conv_put<0>(aL[0],aL[1],e0,sb,warp,lane);
      conv_get<0>(xr,ar,sb,warp,lane);
      __syncwarp();
      if(lane==0){ mbar_arrive(bar+8*(B_HD+1)); mbar_arrive(bar+8*(B_WEMPTY+5)); }
      STAMP(88+wg);
    }
    if(wg==1 && wq<3){
      mbar_wait(bar+8*(B_WFULL+SKW+(rt&1)), 0);
      const int j = tid-128;
      const uint32_t par = lds32(sb+OFF_MISC)&1;
      float c0=0.f,c1=0.f,c2=0.f,c3=0.f;
      const uint32_t cb = sb+OFF_W+(5-SKW-(rt&1))*WSLOT+wq*8192+t*4+maps.upfirst*4096;
      #pragma unroll CSU
      for(int k=0;k<32;k++){
        const uint32_t ad = cb + k*128 + ((g^(k&7))<<4);
        const uint32_t v=lds32(ad), u=lds32(ad+4096-maps.upfirst*8192); c0+=bf_lo(v); c1+=bf_hi(v); c2+=bf_lo(u); c3+=bf_hi(u);
      }
      if(j<88) st_rlx128(&g_csp[(f*16+rt)*88+j], (__float_as_uint(c0)&~1u)|par, __float_as_uint(c1), __float_as_uint(c2), __float_as_uint(c3));
      __syncwarp();
      STAMP(73);
    }
    if(warp==7){ if(elect_one()){ first_x(maps, sb, 1); mbar_arrive(bar+8*(B_INIT+1)); } __syncwarp(); STAMP(94); }
    const uint32_t xempty_cl = mapa(bar+8*(B_XEMPTY+wg*NX), lane&1);
    float ag[88], au[88];
    const uint32_t xbase = sb+OFF_X+wg*NX*XSLOT, rbase = sb+(wg? OFF_RES1:OFF_RES0);
    const uint32_t rfrag = rbase+((lane&7)+8*(lane>>4))*128+(((2*wq+((lane>>3)&1))^(lane&7))<<4);
    constexpr uint64_t DHI_A = (uint64_t)0x40000040u<<32, DHI_B = DHI_A | (512u<<16);
    const uint32_t og = maps.upfirst*256, ou = 256-og;
    uint32_t wb = bar+8*wg*(SKW%NS), ph = wg*(SKW/NS), dbl = (((sb+OFF_W+(5-wg*(SKW%NS))*WSLOT)&0x3FFFF)>>4), dal = (xbase&0x3FFFF)>>4, xb = bar+8*(B_XFULL+wg*NX), pwb = 0;
    uint32_t relm = lane==0? 0xff : lane==1? (wg? (0xff00>>(SKW/2))&0xff : (1<<(SKW/2))-1) : 0;
#define G1_STAGE(DA,DB,ACC) { wg_fence(); wgmma_ss<176,1,1>(ag, DA, DHI_B|((DB)+og), ACC); wgmma_ss<176,1,1>(au, DA, DHI_B|((DB)+ou), ACC); wgmma_ss<176,1,1>(ag, (DA)+128, DHI_B|((DB)+og+128), 1); wgmma_ss<176,1,1>(au, (DA)+128, DHI_B|((DB)+ou+128), 1); wg_commit(); }
    {
      mbar_wait(wb, ph);
      if(!x_ok){
        mbar_wait(xb, 0);
        STAMP(wg? 47:45);
        if(x_bad(sb, wg, wq, lane)){
          const uint32_t par = lds32(sb+OFF_MISC), co = lane*128+(((2*wq)^(lane&7))<<4);
          #pragma unroll 1
          for(int tl=0;tl<4;tl++){
            const bf16* src = g_hT+((tl<3? ((rt>>1)+wg*(SKW/2)+tl)&7 : rank*4+fp)*64+lane)*2048+wg*1024+rt*64+wq*16;
            uint4 v[4]; int n=0;
            do{
              #pragma unroll
              for(int i=0;i<4;i++) ld_rlx128(src+(i>>1)*32*2048+(i&1)*8, v[i]);
            }while((((v[0].x^par)|(v[1].x^par)|(v[2].x^par)|(v[3].x^par))&1) && ++n<2000000);
            #pragma unroll
            for(int i=0;i<4;i++) sts128(((tl<3? xbase+tl*8192 : rbase)+(i>>1)*4096+co)^((i&1)<<4), v[i].x,v[i].y,v[i].z,v[i].w);
          }
          asm volatile("fence.proxy.async.shared::cta;":::"memory");
          __syncwarp();
        }
      }
      STAMP(1+wg*16);
      #pragma unroll
      for(int i=0;i<88;i++){ ag[i]=0.f; au[i]=0.f; }
      G1_STAGE(DHI_A|dal, dbl, 0)
    }
    uint32_t okb = mbar_test(wb+8, ph);
    #pragma unroll 1
    for(int xi=0; xi<8; xi++){
      if(!okb) mbar_wait(wb+8, ph);
      G1_STAGE(DHI_A|(dal+256), dbl-WSLOT/16, 1)
      pwb = wb;
      const bool wrap = wb==bar+8*4;
      wb = wrap? bar : wb+16; dbl = wrap? dbl+4*(WSLOT/16) : dbl-2*(WSLOT/16); ph ^= wrap;
      dal = (xi==3)? dal-3*512 : dal+512; xb = (xi==3)? xb-24 : xb+8;
      const uint32_t oka = mbar_test(xb, xi>=3) & mbar_test(wb, ph);
      if(xi==(wg? STX1:STX0)){
        float s0=0.f,s1=0.f,q0=0.f,q1=0.f;
        #pragma unroll
        for(int kk=0;kk<4;kk++){
          uint32_t r[4]; ldsm4t(rfrag+kk*2048, r[0],r[1],r[2],r[3]);
          #pragma unroll
          for(int i=0;i<4;i++){ const float lo=bf_lo(r[i]), hi=bf_hi(r[i]); if(i&1){ s1+=lo+hi; q1=fmaf(lo,lo,fmaf(hi,hi,q1)); } else { s0+=lo+hi; q0=fmaf(lo,lo,fmaf(hi,hi,q0)); } }
        }
        #pragma unroll
        for(int o=1;o<4;o<<=1){ s0+=__shfl_xor_sync(~0u,s0,o); q0+=__shfl_xor_sync(~0u,q0,o); s1+=__shfl_xor_sync(~0u,s1,o); q1+=__shfl_xor_sync(~0u,q1,o); }
        if(t==0) st_rlx128(&g_stat[((rt*2+wg)*8+f)*32+wq*8+g], (__float_as_uint(s0)&~1u)|(lds32(sb+OFF_MISC)&1), __float_as_uint(q0), __float_as_uint(s1), __float_as_uint(q1));
        __syncwarp();
        if(tid==wg*128) mbar_arrive(bar+8*(B_RT+wg));
      }
      uint32_t rel = relm&1; relm>>=1; uint32_t xpar = xi>=3;
      asm volatile("":"+r"(rel),"+r"(xpar));
      wg_wait<1>();
      if(rel) mbar_arrive(pwb+8*B_WEMPTY);
      if(xi==7) break;
      if(!oka){ mbar_wait(xb, xpar); mbar_wait(wb, ph); }
      G1_STAGE(DHI_A|dal, dbl, 1)
      okb = mbar_test(wb+8, ph);
      wg_wait<1>();
      if(rel) mbar_arrive(pwb+8*B_WEMPTY+8);
      if((lane>>1)==1 && xi<4) mbar_arrive_cl(xempty_cl+8*xi);
      if(xi==6 && lane==0) mbar_arrive_cl(mapa(bar+8*(B_PRDY+wg), rank^1));
    }
    mbar_wait(bar+8*(B_PAR+wg), 0);
    mbar_wait(bar+8*(B_PRDY+wg), 0);
    const float4 p0=*(const float4*)(smem_raw+OFF_ROW+(wg*32+wq*8+g)*16);
    const float nm0=p0.x, r0=p0.y, nm1=p0.z, r1=p0.w;
    wg_wait<0>();
    STAMP(2+wg*16);
    if(lane==0){ mbar_arrive_n(pwb+8*B_WEMPTY+8, (wg && SKW)? 2:1); }
    uint32_t act[44], actp[44];
    const float sc0=0.5f*r0*r0, sc1=0.5f*r1*r1;
    const uint32_t adst = mapa(xbase+(3-wq)*2048+lane*16, rank^1), abar = mapa(bar+8*(B_AFULL+wg), rank^1);
    {
      const float4* cs = (const float4*)(smem_raw+OFF_CS);
      const float h0=0.5f*r0, h1=0.5f*r1;
      #pragma unroll
      for(int j=0;j<22;j++){
        const float4 c4=cs[4*j+t];
        const float g0=fmaf(nm0,c4.x,ag[4*j+0]), g1=fmaf(nm0,c4.y,ag[4*j+1]), g2=fmaf(nm1,c4.x,ag[4*j+2]), g3=fmaf(nm1,c4.y,ag[4*j+3]);
        const float y0=g0*fmaf(nm0,c4.z,au[4*j+0]), y1=g1*fmaf(nm0,c4.w,au[4*j+1]), y2=g2*fmaf(nm1,c4.z,au[4*j+2]), y3=g3*fmaf(nm1,c4.w,au[4*j+3]);
        act[2*j]  =pack_bf16(y0*fmaf(sc0,tanh_fast(g0*h0),sc0), y1*fmaf(sc0,tanh_fast(g1*h0),sc0));
        act[2*j+1]=pack_bf16(y2*fmaf(sc1,tanh_fast(g2*h1),sc1), y3*fmaf(sc1,tanh_fast(g3*h1),sc1));
        if((j%3)==2 && j/3<NIN){ const int kk=j/3; st_async128(adst+(kk>>2)*8192+(kk&3)*512, act[4*kk],act[4*kk+1],act[4*kk+2],act[4*kk+3], abar); }
      }
    }
    STAMP(3+wg*16);
    #pragma unroll
    for(int kk=NIN;kk<11;kk++) st_async128(adst+(kk>>2)*8192+(kk&3)*512, act[4*kk],act[4*kk+1],act[4*kk+2],act[4*kk+3], abar);
    float acc2[2][32];
    #pragma unroll
    for(int i=0;i<32;i++){ acc2[0][i]=0.f; acc2[1][i]=0.f; }
    const uint32_t wbase = xbase+(3-wq)*2048;
    const uint32_t srow = ((~lane&4)<<1) | ((~lane&1)<<2) | (lane&2) | ((lane>>3)&1);
    const int orow = pos2row(wg*1024+rt*64+wq*16+5);
    uint32_t hr[16];
    #pragma unroll
    for(int kk=0;kk<4;kk++) ldsm4t(rfrag+kk*2048, hr[4*kk],hr[4*kk+1],hr[4*kk+2],hr[4*kk+3]);
    auto stage=[&](const float* a, int c){
      #pragma unroll
      for(int kk=0;kk<4;kk++){
        uint32_t o0=pack_bf16(a[8*kk],a[8*kk+1]), o1=pack_bf16(a[8*kk+2],a[8*kk+3]), o2=pack_bf16(a[8*kk+4],a[8*kk+5]), o3=pack_bf16(a[8*kk+6],a[8*kk+7]);
        if(c==0){
          o0=hadd2_bf16(o0,hr[4*kk]); o1=hadd2_bf16(o1,hr[4*kk+1]); o2=hadd2_bf16(o2,hr[4*kk+2]); o3=hadd2_bf16(o3,hr[4*kk+3]);
        }
        stsm4_nm(wbase+c*8192+srow*128+(((2*kk+(lane>>4))^(srow&7))<<4), o0,o1,o2,o3);
      }
    };
    auto flush=[&](int c, int n){
      asm volatile("fence.proxy.async.shared::cta;":::"memory");
      __syncwarp();
      if(c<HF){ if(lane<2) mbar_arrive(bar+8*(B_XEMPTY+wg*NX+c)); }
      else if(elect_one()){
        tma4d_red_add(&maps.out, rank*256+((fp+c)&3)*64, orow&7, (orow>>3)&15, orow>>7, wbase+c*8192);
        asm volatile("cp.async.bulk.commit_group;":::"memory");
      }
    };
    uint32_t okw = 0;
    #pragma unroll
    for(int i=0;i<8;i++){
      const int ch = (G2_CH>>(4*i))&3, peer = (G2_PEER>>i)&1;
      constexpr int S0=(16+SKW)%NS, P0=((16+SKW)/NS)&1;
      const int slot=(S0+i)%NS, pslot=(S0+i+NS-1)%NS, ph=(P0+(S0+i)/NS)&1;
      if(i==2){
        mbar_wait(bar+8*(B_AFULL+wg), 0);
        #pragma unroll
        for(int kk=0;kk<11;kk++) lds128_nm(wbase+lane*16+(kk>>2)*8192+(kk&3)*512, actp[4*kk],actp[4*kk+1],actp[4*kk+2],actp[4*kk+3]);
      }
      if(!okw) mbar_wait(bar+8*(B_WFULL+slot), ph);
      if(i<7) okw = mbar_test(bar+8*(B_WFULL+(S0+i+1)%NS), (P0+(S0+i+1)/NS)&1);
      if(i==2 || i==4 || i==6 || (i==0 && wg==1)) asm volatile("bar.sync %0, 256;"::"r"(2+wg):"memory");
      const uint64_t db = make_desc(sb+OFF_W+(5-slot)*WSLOT, 0, 1024, 1);
      wg_fence();
      #pragma unroll
      for(int kk=0;kk<11;kk++){
        if(peer) wgmma_rs<64,1>(acc2[ch&1], actp[4*kk],actp[4*kk+1],actp[4*kk+2],actp[4*kk+3], db+kk*128, 1);
        else     wgmma_rs<64,1>(acc2[ch&1], act[4*kk],act[4*kk+1],act[4*kk+2],act[4*kk+3], db+kk*128, kk>0);
      }
      wg_commit();
      if(i==1 || i==3 || i==5 || (i==7 && wg==0)) asm volatile("bar.arrive %0, 256;"::"r"(3-wg):"memory");
      if(i==1){ wg_wait<0>(); if(lane<2) mbar_arrive(bar+8*(B_WEMPTY+(lane? slot:pslot))); }
      if(i==3){ wg_wait<1>(); stage(acc2[0], 0); flush(0,1); wg_wait<0>(); stage(acc2[1], 1); flush(1,1); }
      if(i==5){ wg_wait<0>(); stage(acc2[0], 2); flush(2,1); }
      STAMP(32+wg*16+i);
    }
    wg_wait<0>();
    STAMP(4+wg*16);
    stage(acc2[1], 3); flush(3,1);
    STAMP(5+wg*16);
    asm volatile("cp.async.bulk.wait_group.read 0;":::"memory");
    STAMP(6+wg*16);
  }
  __syncwarp();
  asm volatile("barrier.cluster.arrive.relaxed.aligned;":::"memory");
  asm volatile("barrier.cluster.wait.aligned;":::"memory");
}

typedef CUresult (*PFN_encodeTiled)(CUtensorMap*, CUtensorMapDataType, cuuint32_t, void*, const cuuint64_t*, const cuuint64_t*, const cuuint32_t*, const cuuint32_t*, CUtensorMapInterleave, CUtensorMapSwizzle, CUtensorMapL2promotion, CUtensorMapFloatOOBfill);
static void make2d(PFN_encodeTiled enc, CUtensorMap* m, const void* p, uint64_t d0, uint64_t d1, uint32_t b0, uint32_t b1){
  cuuint64_t gd[2]={d0,d1}; cuuint64_t gs[1]={d0*2}; cuuint32_t bx[2]={b0,b1}; cuuint32_t es[2]={1,1};
  enc(m,CU_TENSOR_MAP_DATA_TYPE_BFLOAT16,2,(void*)p,gd,gs,bx,es,CU_TENSOR_MAP_INTERLEAVE_NONE,CU_TENSOR_MAP_SWIZZLE_128B,CU_TENSOR_MAP_L2_PROMOTION_L2_128B,CU_TENSOR_MAP_FLOAT_OOB_FILL_NONE);
}
static void make3d(PFN_encodeTiled enc, CUtensorMap* m, const void* p, uint64_t d0, uint64_t d1, uint64_t d2, uint64_t s1, uint64_t s2, uint32_t b0, uint32_t b1, uint32_t b2, CUtensorMapSwizzle sw, CUtensorMapL2promotion pr){
  cuuint64_t gd[3]={d0,d1,d2}; cuuint64_t gs[2]={s1,s2}; cuuint32_t bx[3]={b0,b1,b2}; cuuint32_t es[3]={1,1,1};
  enc(m,CU_TENSOR_MAP_DATA_TYPE_BFLOAT16,3,(void*)p,gd,gs,bx,es,CU_TENSOR_MAP_INTERLEAVE_NONE,sw,pr,CU_TENSOR_MAP_FLOAT_OOB_FILL_NONE);
}

extern "C" void kernel_launch(void* const* d_in, const int* in_sizes, int n_in, void* d_out, int out_size){
  const bf16* q=(const bf16*)d_in[0]; const bf16* k=(const bf16*)d_in[1]; const bf16* v=(const bf16*)d_in[2];
  const bf16* sh=(const bf16*)d_in[3]; const bf16* K=(const bf16*)d_in[4]; const bf16* Dv=(const bf16*)d_in[5];
  const bf16* wgt=(const bf16*)d_in[7]; const bf16* wup=(const bf16*)d_in[8]; const bf16* wdn=(const bf16*)d_in[9];
  void* fn=nullptr; cudaDriverEntryPointQueryResult qr; cudaGetDriverEntryPoint("cuTensorMapEncodeTiled",&fn,cudaEnableDefault,&qr);
  PFN_encodeTiled enc=(PFN_encodeTiled)fn;
  void* hT; cudaGetSymbolAddress(&hT,g_hT);
  Maps maps;
  make3d(enc,&maps.k,k,512,256,8,8192,1024,8,17,8,CU_TENSOR_MAP_SWIZZLE_NONE,CU_TENSOR_MAP_L2_PROMOTION_L2_128B);
  make3d(enc,&maps.v,v,512,256,8,8192,1024,8,16,8,CU_TENSOR_MAP_SWIZZLE_NONE,CU_TENSOR_MAP_L2_PROMOTION_L2_128B);
  { maps.upfirst = wup<wgt; const bf16* w0 = wup<wgt? wup:wgt; const uint64_t dm = (uint64_t)((wup<wgt? wgt-wup : wup-wgt)*2);
    cuuint64_t gd[4]={F_,D_,2,2}; cuuint64_t gs[3]={F_*2,dm,128}; cuuint32_t bx[4]={64,32,2,2}; cuuint32_t es[4]={1,1,1,1};
    enc(&maps.w64,CU_TENSOR_MAP_DATA_TYPE_BFLOAT16,4,(void*)w0,gd,gs,bx,es,CU_TENSOR_MAP_INTERLEAVE_NONE,CU_TENSOR_MAP_SWIZZLE_128B,CU_TENSOR_MAP_L2_PROMOTION_L2_128B,CU_TENSOR_MAP_FLOAT_OOB_FILL_NONE);
    make3d(enc,&maps.w48,w0,F_,D_,2,F_*2,dm,48,32,2,CU_TENSOR_MAP_SWIZZLE_128B,CU_TENSOR_MAP_L2_PROMOTION_L2_128B); }
  make2d(enc,&maps.wd,wdn,D_,F_,64,176);
  make2d(enc,&maps.ht,hT,S_,D_,64,32);
  { cuuint64_t gd[4]={512,8,16,16}; cuuint64_t gs[3]={1024,8192,131072}; cuuint32_t bx[4]={64,2,4,2}; cuuint32_t es[4]={1,1,1,1};
    enc(&maps.out,CU_TENSOR_MAP_DATA_TYPE_BFLOAT16,4,d_out,gd,gs,bx,es,CU_TENSOR_MAP_INTERLEAVE_NONE,CU_TENSOR_MAP_SWIZZLE_128B,CU_TENSOR_MAP_L2_PROMOTION_NONE,CU_TENSOR_MAP_FLOAT_OOB_FILL_NONE);
    bx[3]=8; enc(&maps.out8,CU_TENSOR_MAP_DATA_TYPE_BFLOAT16,4,d_out,gd,gs,bx,es,CU_TENSOR_MAP_INTERLEAVE_NONE,CU_TENSOR_MAP_SWIZZLE_128B,CU_TENSOR_MAP_L2_PROMOTION_NONE,CU_TENSOR_MAP_FLOAT_OOB_FILL_NONE); }
  void* xa; cudaGetSymbolAddress(&xa,g_xa);
  make2d(enc,&maps.xa,xa,8192,128,64,128);
  cudaFuncSetAttribute(fused_kernel,cudaFuncAttributeMaxDynamicSharedMemorySize,SMEM_BYTES);
  fused_kernel<<<128,384,SMEM_BYTES>>>(maps,q,sh,K,Dv,wdn,(bf16*)d_out);
}
```

```cpp
#include <cuda_runtime.h>
#include <cuda_bf16.h>
#include <cuda.h>
#include <stdint.h>

template<int TA,int TB> __device__ __forceinline__ void wgmma_ss_n176(float* d, uint64_t da, uint64_t db, int sd){
  asm volatile("{ .reg .pred p; setp.ne.b32 p, %90, 0; wgmma.mma_async.sync.aligned.m64n176k16.f32.bf16.bf16 {%0,%1,%2,%3,%4,%5,%6,%7,%8,%9,%10,%11,%12,%13,%14,%15,%16,%17,%18,%19,%20,%21,%22,%23,%24,%25,%26,%27,%28,%29,%30,%31,%32,%33,%34,%35,%36,%37,%38,%39,%40,%41,%42,%43,%44,%45,%46,%47,%48,%49,%50,%51,%52,%53,%54,%55,%56,%57,%58,%59,%60,%61,%62,%63,%64,%65,%66,%67,%68,%69,%70,%71,%72,%73,%74,%75,%76,%77,%78,%79,%80,%81,%82,%83,%84,%85,%86,%87}, %88, %89, p, 1, 1, %91, %92; }"
   : "+f"(d[0]),"+f"(d[1]),"+f"(d[2]),"+f"(d[3]),"+f"(d[4]),"+f"(d[5]),"+f"(d[6]),"+f"(d[7]),"+f"(d[8]),"+f"(d[9]),"+f"(d[10]),"+f"(d[11]),"+f"(d[12]),"+f"(d[13]),"+f"(d[14]),"+f"(d[15]),"+f"(d[16]),"+f"(d[17]),"+f"(d[18]),"+f"(d[19]),"+f"(d[20]),"+f"(d[21]),"+f"(d[22]),"+f"(d[23]),"+f"(d[24]),"+f"(d[25]),"+f"(d[26]),"+f"(d[27]),"+f"(d[28]),"+f"(d[29]),"+f"(d[30]),"+f"(d[31]),"+f"(d[32]),"+f"(d[33]),"+f"(d[34]),"+f"(d[35]),"+f"(d[36]),"+f"(d[37]),"+f"(d[38]),"+f"(d[39]),"+f"(d[40]),"+f"(d[41]),"+f"(d[42]),"+f"(d[43]),"+f"(d[44]),"+f"(d[45]),"+f"(d[46]),"+f"(d[47]),"+f"(d[48]),"+f"(d[49]),"+f"(d[50]),"+f"(d[51]),"+f"(d[52]),"+f"(d[53]),"+f"(d[54]),"+f"(d[55]),"+f"(d[56]),"+f"(d[57]),"+f"(d[58]),"+f"(d[59]),"+f"(d[60]),"+f"(d[61]),"+f"(d[62]),"+f"(d[63]),"+f"(d[64]),"+f"(d[65]),"+f"(d[66]),"+f"(d[67]),"+f"(d[68]),"+f"(d[69]),"+f"(d[70]),"+f"(d[71]),"+f"(d[72]),"+f"(d[73]),"+f"(d[74]),"+f"(d[75]),"+f"(d[76]),"+f"(d[77]),"+f"(d[78]),"+f"(d[79]),"+f"(d[80]),"+f"(d[81]),"+f"(d[82]),"+f"(d[83]),"+f"(d[84]),"+f"(d[85]),"+f"(d[86]),"+f"(d[87]) : "l"(da), "l"(db), "r"(sd), "n"(TA), "n"(TB));
}
template<int TB> __device__ __forceinline__ void wgmma_rs_n8(float* d, uint32_t a0, uint32_t a1, uint32_t a2, uint32_t a3, uint64_t db, int sd){
  asm volatile("{ .reg .pred p; setp.ne.b32 p, %9, 0; wgmma.mma_async.sync.aligned.m64n8k16.f32.bf16.bf16 {%0,%1,%2,%3}, {%4,%5,%6,%7}, %8, p, 1, 1, %10; }"
   : "+f"(d[0]),"+f"(d[1]),"+f"(d[2]),"+f"(d[3]) : "r"(a0),"r"(a1),"r"(a2),"r"(a3), "l"(db), "r"(sd), "n"(TB));
}
template<int TB> __device__ __forceinline__ void wgmma_rs_n16(float* d, uint32_t a0, uint32_t a1, uint32_t a2, uint32_t a3, uint64_t db, int sd){
  asm volatile("{ .reg .pred p; setp.ne.b32 p, %13, 0; wgmma.mma_async.sync.aligned.m64n16k16.f32.bf16.bf16 {%0,%1,%2,%3,%4,%5,%6,%7}, {%8,%9,%10,%11}, %12, p, 1, 1, %14; }"
   : "+f"(d[0]),"+f"(d[1]),"+f"(d[2]),"+f"(d[3]),"+f"(d[4]),"+f"(d[5]),"+f"(d[6]),"+f"(d[7]) : "r"(a0),"r"(a1),"r"(a2),"r"(a3), "l"(db), "r"(sd), "n"(TB));
}
template<int TB> __device__ __forceinline__ void wgmma_rs_n24(float* d, uint32_t a0, uint32_t a1, uint32_t a2, uint32_t a3, uint64_t db, int sd){
  asm volatile("{ .reg .pred p; setp.ne.b32 p, %17, 0; wgmma.mma_async.sync.aligned.m64n24k16.f32.bf16.bf16 {%0,%1,%2,%3,%4,%5,%6,%7,%8,%9,%10,%11}, {%12,%13,%14,%15}, %16, p, 1, 1, %18; }"
   : "+f"(d[0]),"+f"(d[1]),"+f"(d[2]),"+f"(d[3]),"+f"(d[4]),"+f"(d[5]),"+f"(d[6]),"+f"(d[7]),"+f"(d[8]),"+f"(d[9]),"+f"(d[10]),"+f"(d[11]) : "r"(a0),"r"(a1),"r"(a2),"r"(a3), "l"(db), "r"(sd), "n"(TB));
}
template<int TB> __device__ __forceinline__ void wgmma_rs_n32(float* d, uint32_t a0, uint32_t a1, uint32_t a2, uint32_t a3, uint64_t db, int sd){
  asm volatile("{ .reg .pred p; setp.ne.b32 p, %21, 0; wgmma.mma_async.sync.aligned.m64n32k16.f32.bf16.bf16 {%0,%1,%2,%3,%4,%5,%6,%7,%8,%9,%10,%11,%12,%13,%14,%15}, {%16,%17,%18,%19}, %20, p, 1, 1, %22; }"
   : "+f"(d[0]),"+f"(d[1]),"+f"(d[2]),"+f"(d[3]),"+f"(d[4]),"+f"(d[5]),"+f"(d[6]),"+f"(d[7]),"+f"(d[8]),"+f"(d[9]),"+f"(d[10]),"+f"(d[11]),"+f"(d[12]),"+f"(d[13]),"+f"(d[14]),"+f"(d[15]) : "r"(a0),"r"(a1),"r"(a2),"r"(a3), "l"(db), "r"(sd), "n"(TB));
}
template<int TB> __device__ __forceinline__ void wgmma_rs_n40(float* d, uint32_t a0, uint32_t a1, uint32_t a2, uint32_t a3, uint64_t db, int sd){
  asm volatile("{ .reg .pred p; setp.ne.b32 p, %25, 0; wgmma.mma_async.sync.aligned.m64n40k16.f32.bf16.bf16 {%0,%1,%2,%3,%4,%5,%6,%7,%8,%9,%10,%11,%12,%13,%14,%15,%16,%17,%18,%19}, {%20,%21,%22,%23}, %24, p, 1, 1, %26; }"
   : "+f"(d[0]),"+f"(d[1]),"+f"(d[2]),"+f"(d[3]),"+f"(d[4]),"+f"(d[5]),"+f"(d[6]),"+f"(d[7]),"+f"(d[8]),"+f"(d[9]),"+f"(d[10]),"+f"(d[11]),"+f"(d[12]),"+f"(d[13]),"+f"(d[14]),"+f"(d[15]),"+f"(d[16]),"+f"(d[17]),"+f"(d[18]),"+f"(d[19]) : "r"(a0),"r"(a1),"r"(a2),"r"(a3), "l"(db), "r"(sd), "n"(TB));
}
template<int TB> __device__ __forceinline__ void wgmma_rs_n48(float* d, uint32_t a0, uint32_t a1, uint32_t a2, uint32_t a3, uint64_t db, int sd){
  asm volatile("{ .reg .pred p; setp.ne.b32 p, %29, 0; wgmma.mma_async.sync.aligned.m64n48k16.f32.bf16.bf16 {%0,%1,%2,%3,%4,%5,%6,%7,%8,%9,%10,%11,%12,%13,%14,%15,%16,%17,%18,%19,%20,%21,%22,%23}, {%24,%25,%26,%27}, %28, p, 1, 1, %30; }"
   : "+f"(d[0]),"+f"(d[1]),"+f"(d[2]),"+f"(d[3]),"+f"(d[4]),"+f"(d[5]),"+f"(d[6]),"+f"(d[7]),"+f"(d[8]),"+f"(d[9]),"+f"(d[10]),"+f"(d[11]),"+f"(d[12]),"+f"(d[13]),"+f"(d[14]),"+f"(d[15]),"+f"(d[16]),"+f"(d[17]),"+f"(d[18]),"+f"(d[19]),"+f"(d[20]),"+f"(d[21]),"+f"(d[22]),"+f"(d[23]) : "r"(a0),"r"(a1),"r"(a2),"r"(a3), "l"(db), "r"(sd), "n"(TB));
}
template<int TB> __device__ __forceinline__ void wgmma_rs_n56(float* d, uint32_t a0, uint32_t a1, uint32_t a2, uint32_t a3, uint64_t db, int sd){
  asm volatile("{ .reg .pred p; setp.ne.b32 p, %33, 0; wgmma.mma_async.sync.aligned.m64n56k16.f32.bf16.bf16 {%0,%1,%2,%3,%4,%5,%6,%7,%8,%9,%10,%11,%12,%13,%14,%15,%16,%17,%18,%19,%20,%21,%22,%23,%24,%25,%26,%27}, {%28,%29,%30,%31}, %32, p, 1, 1, %34; }"
   : "+f"(d[0]),"+f"(d[1]),"+f"(d[2]),"+f"(d[3]),"+f"(d[4]),"+f"(d[5]),"+f"(d[6]),"+f"(d[7]),"+f"(d[8]),"+f"(d[9]),"+f"(d[10]),"+f"(d[11]),"+f"(d[12]),"+f"(d[13]),"+f"(d[14]),"+f"(d[15]),"+f"(d[16]),"+f"(d[17]),"+f"(d[18]),"+f"(d[19]),"+f"(d[20]),"+f"(d[21]),"+f"(d[22]),"+f"(d[23]),"+f"(d[24]),"+f"(d[25]),"+f"(d[26]),"+f"(d[27]) : "r"(a0),"r"(a1),"r"(a2),"r"(a3), "l"(db), "r"(sd), "n"(TB));
}
template<int TB> __device__ __forceinline__ void wgmma_rs_n64(float* d, uint32_t a0, uint32_t a1, uint32_t a2, uint32_t a3, uint64_t db, int sd){
  asm volatile("{ .reg .pred p; setp.ne.b32 p, %37, 0; wgmma.mma_async.sync.aligned.m64n64k16.f32.bf16.bf16 {%0,%1,%2,%3,%4,%5,%6,%7,%8,%9,%10,%11,%12,%13,%14,%15,%16,%17,%18,%19,%20,%21,%22,%23,%24,%25,%26,%27,%28,%29,%30,%31}, {%32,%33,%34,%35}, %36, p, 1, 1, %38; }"
   : "+f"(d[0]),"+f"(d[1]),"+f"(d[2]),"+f"(d[3]),"+f"(d[4]),"+f"(d[5]),"+f"(d[6]),"+f"(d[7]),"+f"(d[8]),"+f"(d[9]),"+f"(d[10]),"+f"(d[11]),"+f"(d[12]),"+f"(d[13]),"+f"(d[14]),"+f"(d[15]),"+f"(d[16]),"+f"(d[17]),"+f"(d[18]),"+f"(d[19]),"+f"(d[20]),"+f"(d[21]),"+f"(d[22]),"+f"(d[23]),"+f"(d[24]),"+f"(d[25]),"+f"(d[26]),"+f"(d[27]),"+f"(d[28]),"+f"(d[29]),"+f"(d[30]),"+f"(d[31]) : "r"(a0),"r"(a1),"r"(a2),"r"(a3), "l"(db), "r"(sd), "n"(TB));
}
template<int N,int TA,int TB> __device__ __forceinline__ void wgmma_ss(float* d, uint64_t da, uint64_t db, int sd){
  if constexpr(N==176) wgmma_ss_n176<TA,TB>(d,da,db,sd);
}
template<int N,int TB> __device__ __forceinline__ void wgmma_rs(float* d, uint32_t a0,uint32_t a1,uint32_t a2,uint32_t a3, uint64_t db, int sd){
  if constexpr(N==8) wgmma_rs_n8<TB>(d,a0,a1,a2,a3,db,sd);
  if constexpr(N==16) wgmma_rs_n16<TB>(d,a0,a1,a2,a3,db,sd);
  if constexpr(N==24) wgmma_rs_n24<TB>(d,a0,a1,a2,a3,db,sd);
  if constexpr(N==32) wgmma_rs_n32<TB>(d,a0,a1,a2,a3,db,sd);
  if constexpr(N==40) wgmma_rs_n40<TB>(d,a0,a1,a2,a3,db,sd);
  if constexpr(N==48) wgmma_rs_n48<TB>(d,a0,a1,a2,a3,db,sd);
  if constexpr(N==56) wgmma_rs_n56<TB>(d,a0,a1,a2,a3,db,sd);
  if constexpr(N==64) wgmma_rs_n64<TB>(d,a0,a1,a2,a3,db,sd);
}

typedef __nv_bfloat16 bf16;
constexpr int S_ = 2048, D_ = 512, F_ = 1376, FS = 176;

__device__ __forceinline__ uint32_t smem_u32(const void* p){ return (uint32_t)__cvta_generic_to_shared(p); }
__device__ __forceinline__ void mbar_init(uint32_t bar, uint32_t cnt){ asm volatile("mbarrier.init.shared::cta.b64 [%0], %1;"::"r"(bar),"r"(cnt):"memory"); }
__device__ __forceinline__ void mbar_expect_tx(uint32_t bar, uint32_t bytes){ asm volatile("mbarrier.arrive.expect_tx.shared::cta.b64 _, [%0], %1;"::"r"(bar),"r"(bytes):"memory"); }
__device__ __forceinline__ void mbar_arrive(uint32_t bar){ asm volatile("mbarrier.arrive.shared::cta.b64 _, [%0];"::"r"(bar):"memory"); }
__device__ __forceinline__ void mbar_arrive_n(uint32_t bar, uint32_t n){ asm volatile("mbarrier.arrive.shared::cta.b64 _, [%0], %1;"::"r"(bar),"r"(n):"memory"); }
__device__ __forceinline__ void mbar_arrive_cl(uint32_t cbar){ asm volatile("mbarrier.arrive.shared::cluster.b64 _, [%0];"::"r"(cbar):"memory"); }
__device__ __forceinline__ uint32_t mapa(uint32_t a, uint32_t cta){ uint32_t r; asm volatile("mapa.shared::cluster.u32 %0, %1, %2;":"=r"(r):"r"(a),"r"(cta)); return r; }
__device__ __forceinline__ void mbar_wait(uint32_t bar, uint32_t ph){
  asm volatile("{ .reg .pred p; .reg .u32 c; mov.u32 c, 0;\n"
               "WL: mbarrier.try_wait.parity.shared::cta.b64 p, [%0], %1; @p bra WD; add.u32 c,c,1; setp.lt.u32 p, c, 1000000; @p bra WL; trap;\n"
               "WD: }"::"r"(bar),"r"(ph):"memory"); }
__device__ __forceinline__ uint32_t mbar_test(uint32_t bar, uint32_t ph){ uint32_t ok; asm volatile("{ .reg .pred p; mbarrier.test_wait.parity.shared::cta.b64 p, [%1], %2; selp.u32 %0,1,0,p; }":"=r"(ok):"r"(bar),"r"(ph):"memory"); return ok; }
__device__ __forceinline__ void spin_guard(int n){ asm volatile("{ .reg .pred p; setp.gt.s32 p, %0, 2000000; @p trap; }"::"r"(n)); }
__device__ __forceinline__ bool elect_one(){ uint32_t p; asm volatile("{ .reg .pred P; elect.sync _|P, 0xffffffff; selp.u32 %0,1,0,P; }":"=r"(p)); return p; }
__device__ __forceinline__ void tma2d(uint32_t dst, const CUtensorMap* m, int c0, int c1, uint32_t bar){
  asm volatile("cp.async.bulk.tensor.2d.shared::cluster.global.mbarrier::complete_tx::bytes [%0], [%1, {%3, %4}], [%2];"::"r"(dst),"l"(m),"r"(bar),"r"(c0),"r"(c1):"memory"); }
__device__ __forceinline__ void tma2d_mc(uint32_t dst, const CUtensorMap* m, int c0, int c1, uint32_t bar){
  asm volatile("cp.async.bulk.tensor.2d.shared::cluster.global.mbarrier::complete_tx::bytes.multicast::cluster [%0], [%1, {%3, %4}], [%2], %5;"::"r"(dst),"l"(m),"r"(bar),"r"(c0),"r"(c1),"h"((uint16_t)3):"memory"); }
__device__ __forceinline__ void wg_fence(){ asm volatile("wgmma.fence.sync.aligned;":::"memory"); }
__device__ __forceinline__ void wg_commit(){ asm volatile("wgmma.commit_group.sync.aligned;":::"memory"); }
template<int N> __device__ __forceinline__ void wg_wait(){ asm volatile("wgmma.wait_group.sync.aligned %0;"::"n"(N):"memory"); }
__device__ __forceinline__ uint64_t make_desc(uint32_t addr, uint32_t lbo, uint32_t sbo, uint32_t sw){ return (uint64_t)((addr&0x3FFFF)>>4) | ((uint64_t)((lbo&0x3FFFF)>>4)<<16) | ((uint64_t)((sbo&0x3FFFF)>>4)<<32) | ((uint64_t)sw<<62); }
__device__ __forceinline__ void ldsm4t(uint32_t a, uint32_t& r0, uint32_t& r1, uint32_t& r2, uint32_t& r3){ asm volatile("ldmatrix.sync.aligned.m8n8.x4.trans.shared.b16 {%0,%1,%2,%3}, [%4];":"=r"(r0),"=r"(r1),"=r"(r2),"=r"(r3):"r"(a):"memory"); }
__device__ __forceinline__ uint32_t pack_bf16(float lo, float hi){ uint32_t r; asm("cvt.rn.bf16x2.f32 %0, %1, %2;":"=r"(r):"f"(hi),"f"(lo)); return r; }
__device__ __forceinline__ float bf_lo(uint32_t v){ return __uint_as_float(v<<16); }
__device__ __forceinline__ float bf_hi(uint32_t v){ return __uint_as_float(v&0xffff0000u); }
__device__ __forceinline__ float rbf(float x){ return __bfloat162float(__float2bfloat16(x)); }
__device__ __forceinline__ uint32_t hadd2_bf16(uint32_t a, uint32_t b){ uint32_t r; asm("add.rn.bf16x2 %0, %1, %2;":"=r"(r):"r"(a),"r"(b)); return r; }
__device__ __forceinline__ float tanh_fast(float x){ float r; asm("tanh.approx.f32 %0, %1;":"=f"(r):"f"(x)); return r; }

__device__ __forceinline__ void st_rlx128(void* p, uint32_t a, uint32_t b, uint32_t c, uint32_t d){
  asm volatile("{ .reg .b64 l,h; .reg .b128 v; mov.b64 l,{%1,%2}; mov.b64 h,{%3,%4}; mov.b128 v,{l,h}; st.relaxed.gpu.global.b128 [%0], v; }"::"l"(p),"r"(a),"r"(b),"r"(c),"r"(d):"memory"); }
__device__ __forceinline__ void ld_rlx128(const void* p, uint4& v){
  asm volatile("{ .reg .b64 l,h; .reg .b128 v; ld.relaxed.gpu.global.b128 v, [%4]; mov.b128 {l,h}, v; mov.b64 {%0,%1}, l; mov.b64 {%2,%3}, h; }":"=r"(v.x),"=r"(v.y),"=r"(v.z),"=r"(v.w):"l"(p):"memory"); }
__device__ __forceinline__ void st_async128(uint32_t dst, uint32_t a, uint32_t b, uint32_t c, uint32_t d, uint32_t cbar){
  asm volatile("st.async.weak.shared::cluster.mbarrier::complete_tx::bytes.v4.b32 [%0], {%1,%2,%3,%4}, [%5];"::"r"(dst),"r"(a),"r"(b),"r"(c),"r"(d),"r"(cbar)); }
__device__ __forceinline__ void bulk_g2s(uint32_t dst, const void* src, uint32_t bytes, uint32_t bar){
  asm volatile("cp.async.bulk.shared::cluster.global.mbarrier::complete_tx::bytes [%0], [%1], %2, [%3];"::"r"(dst),"l"(src),"r"(bytes),"r"(bar):"memory"); }
__device__ __forceinline__ void lds128(uint32_t a, uint32_t& x, uint32_t& y, uint32_t& z, uint32_t& w){ asm volatile("ld.shared.v4.u32 {%0,%1,%2,%3}, [%4];":"=r"(x),"=r"(y),"=r"(z),"=r"(w):"r"(a):"memory"); }
__device__ __forceinline__ void tma4d_red_add(const CUtensorMap* m, int c0, int c1, int c2, int c3, uint32_t src){
  asm volatile("cp.reduce.async.bulk.tensor.4d.global.shared::cta.add.tile.bulk_group [%0, {%1, %2, %3, %4}], [%5];"::"l"(m),"r"(c0),"r"(c1),"r"(c2),"r"(c3),"r"(src):"memory"); }
__device__ __forceinline__ void stsm4_nm(uint32_t a, uint32_t r0, uint32_t r1, uint32_t r2, uint32_t r3){ asm volatile("stmatrix.sync.aligned.m8n8.x4.shared.b16 [%0], {%1,%2,%3,%4};"::"r"(a),"r"(r0),"r"(r1),"r"(r2),"r"(r3)); }
__device__ __forceinline__ void tma3d(uint32_t dst, const CUtensorMap* m, int c0, int c1, int c2, uint32_t bar){
  asm volatile("cp.async.bulk.tensor.3d.shared::cluster.global.mbarrier::complete_tx::bytes [%0], [%1, {%3, %4, %5}], [%2];"::"r"(dst),"l"(m),"r"(bar),"r"(c0),"r"(c1),"r"(c2):"memory"); }
__device__ __forceinline__ uint32_t lds32(uint32_t a){ uint32_t v; asm volatile("ld.shared.u32 %0, [%1];":"=r"(v):"r"(a)); return v; }
__device__ __forceinline__ void sts128(uint32_t a, uint32_t x, uint32_t y, uint32_t z, uint32_t w){ asm volatile("st.shared.v4.u32 [%0], {%1,%2,%3,%4};"::"r"(a),"r"(x),"r"(y),"r"(z),"r"(w):"memory"); }
__device__ __forceinline__ uint4 ldg_nc128(const void* p){ uint4 v; asm volatile("ld.global.nc.L1::no_allocate.v4.u32 {%0,%1,%2,%3}, [%4];":"=r"(v.x),"=r"(v.y),"=r"(v.z),"=r"(v.w):"l"(p)); return v; }
__device__ __forceinline__ uint32_t hmul2_bf16(uint32_t a, uint32_t b){ uint32_t r; asm("mul.rn.bf16x2 %0, %1, %2;":"=r"(r):"r"(a),"r"(b)); return r; }
__device__ __forceinline__ uint32_t hfma2_bf16(uint32_t a, uint32_t b, uint32_t c){ uint32_t r; asm("fma.rn.bf16x2 %0, %1, %2, %3;":"=r"(r):"r"(a),"r"(b),"r"(c)); return r; }
__device__ __forceinline__ uint32_t hsub2_bf16(uint32_t a, uint32_t b){ uint32_t r; asm("sub.rn.bf16x2 %0, %1, %2;":"=r"(r):"r"(a),"r"(b)); return r; }
__device__ __forceinline__ void signal_add(unsigned* p){ asm volatile("fence.acq_rel.gpu;":::"memory"); asm volatile("red.relaxed.gpu.global.add.u32 [%0], 1;"::"l"(p):"memory"); }
__device__ __forceinline__ void lds128_nm(uint32_t a, uint32_t& x, uint32_t& y, uint32_t& z, uint32_t& w){ asm volatile("ld.shared.v4.u32 {%0,%1,%2,%3}, [%4];":"=r"(x),"=r"(y),"=r"(z),"=r"(w):"r"(a)); }
__device__ __forceinline__ float ln_rstd(float var){
  float sq, r; asm("sqrt.approx.f32 %0, %1;":"=f"(sq):"f"(rbf(rbf(var)+1e-5f))); asm("rcp.approx.f32 %0, %1;":"=f"(r):"f"(rbf(sq))); return r; }
__device__ __forceinline__ float4 gather_sum(const uint4* src, int n, int stride, uint32_t par){
  float4 c=make_float4(0.f,0.f,0.f,0.f);
  #pragma unroll 1
  for(int kb=0;kb<n;kb+=4){
    uint4 v[4]; int it=0;
    do{
      #pragma unroll
      for(int u=0;u<4;u++) ld_rlx128(src+u*stride, v[u]);
      spin_guard(++it);
    }while(((v[0].x^par)|(v[1].x^par)|(v[2].x^par)|(v[3].x^par))&1);
    #pragma unroll
    for(int u=0;u<4;u++){ c.x+=__uint_as_float(v[u].x); c.y+=__uint_as_float(v[u].y); c.z+=__uint_as_float(v[u].z); c.w+=__uint_as_float(v[u].w); }
    src+=4*stride;
  }
  return c;
}
__host__ __device__ __forceinline__ int pos2row(int pos){
  const int P = 1 - (pos >> 10), thr = (pos & 1023) >> 3, k = (pos>>2)&1, h = (pos>>1)&1, e = pos&1;
  const int w = thr >> 5, tp = (thr >> 3)&3, j = (thr >> 1)&3, p = thr & 1;
  return 16*(127 - (64*P + 16*j + 8*k + 2*tp + e)) + 8*h + 2*w + p;
}

__device__ __align__(1024) bf16 g_hT[D_*S_];
__device__ __align__(1024) uint4 g_xa[128*128*8];
__device__ __align__(1024) uint4 g_qs[128*8];
__device__ uint4 g_stat[16*2*8*32];
__device__ uint4 g_csp[8*16*88];
__device__ uint4 g_cs2[8*96];
__device__ unsigned g_cnt[4*32];
#define STAMP(i)

#define QDELAY 2000
#define KV0 3
#define XAFTER 5
#define XPOS 3
#define ZKV 3
#define WSTART 6
#define W9 2
#define PACE 3
#define CSLEEP 600
#define SKW 2
#define STX0 2
#define STX1 2
#define CSUN 4
#define HF 3
#define ENDB 0
#define FORCE_FB 0
#define NIN 7
constexpr int CSU = CSUN;
constexpr uint32_t G2_CH = 0x33221010u, G2_PEER = 0xAC;
constexpr int NS = 6, WSLOT = 24576, NX = 4, XSLOT = 8192;
constexpr int OFF_RES0 = 0, OFF_X = 8192, OFF_RES1 = 73728, OFF_W = 81920;
constexpr int OFF_CS = OFF_W + NS*WSLOT, OFF_ROW = OFF_CS + 2*FS*4, OFF_BAR = OFF_ROW + 1024;
constexpr int TBL = 8320, UPL = 2112, UCH = 2*UPL, QP = 1088, KVCH = 4224;
constexpr int OFF_TBL = 32768, OFF_U = OFF_TBL + 4*TBL, OFF_XAL = 82944, OFF_XAE = OFF_W + 2*WSLOT;
constexpr int OFF_IMG = 0, OFF_X8 = OFF_XAL + 16384, OFF_ZB = OFF_W + WSLOT - 2048, EXB = 32*144;
#define KVOFF(T) (OFF_W + 3*WSLOT + (T)*KVCH - ((T)>>2)*(2*WSLOT+4*KVCH))
constexpr int OFF_KV = OFF_W + 3*WSLOT, OFF_Q = OFF_W + 4*WSLOT;
static_assert(OFF_X8 + EXB <= OFF_ZB && OFF_U + 4*UCH <= OFF_XAL && OFF_XAL + 16384 <= OFF_W + WSLOT, "overlay");
constexpr int B_WFULL = 0, B_WEMPTY = B_WFULL+NS, B_XFULL = B_WEMPTY+NS, B_XEMPTY = B_XFULL+2*NX, B_PRDY = B_XEMPTY+2*NX, B_AFULL = B_PRDY+2,
              B_ONE = B_AFULL+2, B_FB = B_ONE, B_INIT = B_FB+2, B_XA = B_INIT+2, B_PAR = B_XA+2, B_TD = B_PAR+2, B_KV = B_TD+1, B_U = B_KV+8, B_HD = B_U+8, B_Q = B_HD+2, B_QD = B_Q+8, B_SC = B_QD+1, B_X03 = B_SC+1, B_RT = B_X03+1, NBAR = B_RT+2;
constexpr int OFF_MISC = (OFF_BAR + NBAR*8 + 15)&~15;
constexpr int OFF_TGT = OFF_MISC + 16;
constexpr int SMEM_BYTES = OFF_TGT + 16;
static_assert(SMEM_BYTES<=232448,"smem");

struct Maps { CUtensorMap k, v, xa, w64, w48, wd, ht, out, out8; int upfirst; };

__device__ __forceinline__ void load_w_stage(const Maps& maps, uint32_t dst, int col, int k0, uint32_t fb){
  asm volatile("cp.async.bulk.tensor.4d.shared::cluster.global.mbarrier::complete_tx::bytes [%0], [%1, {%3, %4, %5, %5}], [%2];"::"r"(dst),"l"(&maps.w64),"r"(fb),"r"(col),"r"(k0),"r"(0):"memory");
  tma3d(dst+16384, &maps.w48, col+128, k0, 0, fb);
}

template<int N> __device__ __forceinline__ void conv_mma(float* acc, const uint32_t* R, uint64_t db){
  wgmma_rs<N,0>(acc, R[0],R[1],R[2],R[3], db,   1);
  wgmma_rs<N,0>(acc, R[4],R[5],R[6],R[7], db+1, 1);
}
__device__ __forceinline__ void conv_lda(uint32_t* R, const uint32_t* tb, int off){
  R[0]=lds32(tb[0]+off); R[1]=lds32(tb[1]+off); R[3]=lds32(tb[2]+off); R[5]=lds32(tb[3]+off); R[7]=lds32(tb[4]+off);
}
__device__ __forceinline__ void conv_dup(uint32_t* R){
  asm volatile("mov.b32 %0, %1;":"=r"(R[2]):"r"(R[1])); asm volatile("mov.b32 %0, %1;":"=r"(R[4]):"r"(R[3])); asm volatile("mov.b32 %0, %1;":"=r"(R[6]):"r"(R[5]));
}
__device__ __forceinline__ void zero4(float* a){
  #pragma unroll
  for(int i=0;i<4;i+=2) asm volatile("mov.b64 {%0,%1}, 0;":"=f"(a[i]),"=f"(a[i+1]));
}
__device__ __forceinline__ uint32_t tid_now(){ uint32_t t; asm volatile("mov.u32 %0, %%tid.x;":"=r"(t)); return t; }
__device__ __forceinline__ void load_xs(uint4* x, uint4* st, uint32_t sb, int warp, int lane){
  const uint32_t tw = (warp&3)*32+lane, pc = ((warp>>2)*2)^(tw&7);
  #pragma unroll
  for(int i=0;i<4;i++) lds128(sb+OFF_XAL+tw*128+((pc^(i&1)^((i>>1)*4))<<4), x[i].x,x[i].y,x[i].z,x[i].w);
  #pragma unroll
  for(int i=0;i<8;i++) lds128(sb+OFF_XAE+tw*128+((i^(tw&7))<<4), st[i].x,st[i].y,st[i].z,st[i].w);
}
__device__ __forceinline__ void check_xs(uint4* x, uint4* st, uint32_t ep, uint32_t sb, int warp){
  for(int n=0;n<2000000;n++){
    uint32_t bad=0;
    #pragma unroll
    for(int i=0;i<8;i++) bad|=st[i].w^ep;
    if(!bad && x[0].x && x[1].x && x[2].x && x[3].x) break;
    const uint32_t t2=tid_now()&127, pc = ((warp>>2)*2)^(t2&7);
    #pragma unroll
    for(int i=0;i<4;i++) ld_rlx128(&g_xa[blockIdx.x*1024+t2*8+(pc^(i&1)^((i>>1)*4))], x[i]);
    #pragma unroll
    for(int i=0;i<8;i++) ld_rlx128(&g_qs[t2*8+(i^(t2&7))], st[i]);
  }
  __syncwarp();
}
__device__ __forceinline__ void ln_x(uint4* x, const uint4* st, uint4* a){
#define LNA(X,S) ({ const uint32_t d_=hsub2_bf16(X,S.x); hfma2_bf16(d_,S.y,hmul2_bf16(d_,S.z)); })
  #pragma unroll
  for(int i=0;i<2;i++){
    x[i].x=~x[i].x;
    a[i].x=LNA(x[i].x,st[0]); a[i].y=LNA(x[i].y,st[1]); a[i].z=LNA(x[i].z,st[2]); a[i].w=LNA(x[i].w,st[3]);
  }
}
template<int PART> __device__ __forceinline__ uint32_t ex_buf(uint32_t sb, int warp){
  return sb + (PART? (warp<7? OFF_IMG+warp*EXB : OFF_X8) : ((warp&3)<3? OFF_TBL+(warp>>2)*2*TBL+(warp&3)*EXB : OFF_XAL+(warp>>2)*EXB)); }
template<int PART> __device__ __forceinline__ void conv_put(const float* a0, const float* a1, uint4& e0, uint32_t sb, int warp, int lane){
  const uint32_t ad = ex_buf<PART>(sb,warp) + ((lane&24)|((lane&3)<<1)|((lane>>2)&1))*144;
  if(PART) sts128(ad+128, 0,0,0,0); else sts128(ad+128, e0.x,e0.y,e0.z,e0.w);
  #pragma unroll
  for(int ii=0;ii<8;ii++){
    const uint32_t w0=pack_bf16(a0[4*ii],a0[4*ii+1]), w1=pack_bf16(a0[4*ii+2],a0[4*ii+3]), w2=pack_bf16(a1[4*ii],a1[4*ii+1]), w3=pack_bf16(a1[4*ii+2],a1[4*ii+3]);
    sts128(ad+ii*16, w0,w1,w2,w3);
    if(PART && ii==0) e0=make_uint4(w0,w1,w2,w3);
  }
  __syncwarp();
}
template<int PART> __device__ __forceinline__ void conv_get(const uint4* x, const uint4* a, uint32_t sb, int warp, int lane){
  const int cb = blockIdx.x, chl = (warp>>2)*2;
  const uint32_t tw = (warp&3)*32+lane;
  const uint32_t eb = ex_buf<PART>(sb,warp) + (lane&1)*144 + (lane&6)*16 + (lane>>3)*288;
  uint4 d[4][2];
  #pragma unroll
  for(int c=0;c<4;c++){
    const uint32_t ad = eb + c*(8*144+288) - (((lane>>3)+c>3)? 4*288-16 : 0);
    lds128(ad, d[c][0].x,d[c][0].y,d[c][0].z,d[c][0].w);
    lds128(ad+16, d[c][1].x,d[c][1].y,d[c][1].z,d[c][1].w);
  }
#define SUM4(K,F) hadd2_bf16(hadd2_bf16(d[0][K].F,d[1][K].F),hadd2_bf16(d[2][K].F,d[3][K].F))
  uint4 o0, o1;
  o0.x=hadd2_bf16(x[0].x,hmul2_bf16(a[0].x,SUM4(0,x))); o0.y=hadd2_bf16(x[0].y,hmul2_bf16(a[0].y,SUM4(0,y)));
  o0.z=hadd2_bf16(x[0].z,hmul2_bf16(a[0].z,SUM4(1,x))); o0.w=hadd2_bf16(x[0].w,hmul2_bf16(a[0].w,SUM4(1,y)));
  o1.x=hadd2_bf16(x[1].x,hmul2_bf16(a[1].x,SUM4(0,z))); o1.y=hadd2_bf16(x[1].y,hmul2_bf16(a[1].y,SUM4(0,w)));
  o1.z=hadd2_bf16(x[1].z,hmul2_bf16(a[1].z,SUM4(1,z))); o1.w=hadd2_bf16(x[1].w,hmul2_bf16(a[1].w,SUM4(1,w)));
  uint4* dst = (uint4*)(g_hT + (cb*4+chl)*2048 + (1-PART)*1024) + tw;
  const uint32_t par = lds32(sb+OFF_MISC)&1;
  o0.x=(o0.x&~1u)|par; o1.x=(o1.x&~1u)|par;
  dst[0]=o0; dst[256]=o1;
}

__device__ __forceinline__ bool x_bad(uint32_t sb, int wg, int wq, int lane){
  const uint32_t xbase = sb+OFF_X+wg*NX*XSLOT, rbase = sb+(wg? OFF_RES1:OFF_RES0), par = lds32(sb+OFF_MISC), co = lane*128+(((2*wq)^(lane&7))<<4);
  uint32_t bad=0;
  #pragma unroll
  for(int i=0;i<8;i++) bad |= lds32((i<6? xbase+i*4096 : rbase+(i-6)*4096)+co)^par;
  return __any_sync(~0u, bad&1);
}
__device__ __forceinline__ void first_x(const Maps& maps, uint32_t sb, int w){
  const int b = blockIdx.x, rank = b&1, rt = b>>3;
  const uint32_t bar = sb+OFF_BAR, xf = bar+8*(B_XFULL+w*NX), xd = sb+OFF_X+w*NX*XSLOT+rank*4096, rb = sb+(w? OFF_RES1:OFF_RES0);
  const int c0 = w*1024+rt*64, k0 = (rt>>1)+w*(SKW/2), cr = rank*256+((b>>1)&3)*64;
  mbar_expect_tx(xf, 4*XSLOT); mbar_arrive(xf+8); mbar_arrive(xf+16);
  const unsigned tgt = lds32(sb+OFF_TGT+(w? 0:12));
  mbar_wait(bar+8*(B_HD+w), 0);
  {
    unsigned v; int n=0;
    asm volatile("red.relaxed.gpu.global.add.u32 [%0], 1;"::"l"(&g_cnt[w? 0:96]):"memory");
    do{ asm volatile("ld.relaxed.gpu.global.u32 %0, [%1];":"=r"(v):"l"(&g_cnt[w? 0:96]):"memory"); }while((int)(v-tgt)<0 && ++n<2000000);
  }
  tma2d_mc(xd,         &maps.ht, c0, (k0&7)*64+rank*32,     xf);
  tma2d_mc(xd+XSLOT,   &maps.ht, c0, ((k0+1)&7)*64+rank*32, xf);
  tma2d_mc(xd+2*XSLOT, &maps.ht, c0, ((k0+2)&7)*64+rank*32, xf);
  tma2d(rb,      &maps.ht, c0, cr,    xf);
  tma2d(rb+4096, &maps.ht, c0, cr+32, xf);
}

__global__ void __cluster_dims__(2,1,1) __launch_bounds__(384,1)
fused_kernel(const __grid_constant__ Maps maps, const bf16* __restrict__ q, const bf16* __restrict__ shk, const bf16* __restrict__ ssmk,
             const bf16* __restrict__ ssmD, const bf16* __restrict__ wdn, bf16* __restrict__ out){
  extern __shared__ __align__(1024) uint8_t smem_raw[];
  if(threadIdx.x<32){ if(elect_one()){ asm volatile("cp.async.bulk.prefetch.L2.global [%0], 16384;"::"l"(q+blockIdx.x*8192)); } }
  unsigned c_begin; asm volatile("mov.u32 %0, %%clock;":"=r"(c_begin));
  const uint32_t sb = smem_u32(smem_raw);
  const int tid = threadIdx.x, lane = tid&31;
  const int warp = __shfl_sync(0xffffffffu, tid>>5, 0);
  const int wg = warp>>2;
  const int b = blockIdx.x, rank = b&1;
  const int f = b&7, rt = b>>3, fp = f>>1;
  const uint32_t bar = sb+OFF_BAR;

  if(wg==2){
    asm volatile("setmaxnreg.dec.sync.aligned.u32 56;");
    STAMP(58);
    const int cg = b>>1;
    const int cb = cg*2+rank;
    unsigned epoch = 0; uint4 shw = make_uint4(0,0,0,0); uint2 dd = make_uint2(0,0);
    if(warp==11) asm volatile("ld.relaxed.gpu.global.u32 %0, [%1];":"=r"(epoch):"l"(&g_cnt[(lane&3)*32]));
    if(warp!=9){
      shw = ldg_nc128(shk + (cg*8+(lane&3)*2)*4);
      asm volatile("ld.global.nc.v2.u32 {%0,%1}, [%2];":"=r"(dd.x),"=r"(dd.y):"l"(ssmD + cb*4));
    }
    auto ldkv=[&](int i){
      const uint32_t fb=bar+8*(B_KV+i);
      mbar_expect_tx(fb, 2176+2048);
      tma3d(sb+KVOFF(i),      &maps.k, cg*8, i*32+rank*16-1, 0, fb);
      tma3d(sb+KVOFF(i)+2176, &maps.v, cg*8, i*32+rank*16,   0, fb);
    };
    if(warp==9){
      if(lane<3) asm volatile("prefetch.tensormap [%0];"::"l"(&maps.k+lane):"memory");
    }
    STAMP(51+warp);
    asm volatile("bar.sync 0;":::"memory");
    asm volatile("barrier.cluster.arrive.relaxed.aligned;":::"memory");
    if(warp==9){
      { unsigned c1; do{ asm volatile("mov.u32 %0, %%clock;":"=r"(c1)); }while(c1-c_begin<QDELAY); }
      if(elect_one()){
        #pragma unroll
        for(int i=0;i<KV0;i++) ldkv(i);
      }
      __syncwarp();
      mbar_wait(bar+8*B_QD, 0);
      STAMP(79);
      if(elect_one()){
        asm volatile("cp.async.bulk.tensor.2d.global.shared::cta.bulk_group [%0, {%1, %2}], [%3];"::"l"(&maps.xa),"r"(b*64),"r"(0),"r"(sb+OFF_IMG):"memory");
        asm volatile("cp.async.bulk.commit_group;":::"memory");
        #pragma unroll 1
        for(int i=KV0;i<8;i++){
          ldkv(i);
          if(i==XAFTER){
            asm volatile("cp.async.bulk.wait_group.read 0;":::"memory");
            mbar_wait(bar+8*(B_KV+XPOS), 0);
            mbar_expect_tx(bar+8*B_XA, 32768); bulk_g2s(sb+OFF_XAL, &g_xa[cb*1024], 16384, bar+8*B_XA); bulk_g2s(sb+OFF_XAE, g_qs, 16384, bar+8*B_XA);
            STAMP(66);
          }
        }
        mbar_wait(bar+8*B_WEMPTY, 0);
        mbar_wait(bar+8*(B_KV+ZKV), 0);
        #pragma unroll
        for(int i=0;i<8;i++) asm volatile("cp.async.bulk.global.shared::cta.bulk_group [%0], [%1], 2048;"::"l"(out+b*8192+i*1024),"r"(sb+OFF_ZB):"memory");
        asm volatile("cp.async.bulk.commit_group;":::"memory");
        mbar_wait(bar+8*(B_KV+WSTART), 0);
        #pragma unroll 1
        for(int it=0;it<W9;it++){
          mbar_wait(bar+8*(B_WEMPTY+it), 0);
          if(it>=PACE) mbar_wait(bar+8*(B_WFULL+it-PACE), 0);
          mbar_expect_tx(bar+8*(B_WFULL+it), 22528);
          load_w_stage(maps, sb+OFF_W+(5-it)*WSLOT, f*FS, ((it+(rt&14))&15)*32, bar+8*(B_WFULL+it));
          STAMP(24+it);
        }
        asm volatile("cp.async.bulk.wait_group 0;":::"memory");
        asm volatile("fence.proxy.async.global;":::"memory");
        mbar_arrive(bar+8*(B_HD+1));
        STAMP(30);
      }
      __syncwarp();
    }
    if(warp==11){
      asm volatile("":"+r"(epoch));
      epoch = (epoch>>7)+1;
      if(lane<4) asm volatile("st.shared.u32 [%0], %1;"::"r"(sb+OFF_TGT+lane*4),"r"(epoch<<7):"memory");
      if(lane==0) sts128(sb+OFF_MISC, epoch, dd.x, dd.y, 0);
      __syncwarp();
      if(lane==0) mbar_arrive(bar+8*B_SC);
    }
    if(warp==8 && lane<6) asm volatile("prefetch.tensormap [%0];"::"l"(&maps.w64+lane):"memory");
    mbar_wait(bar+8*B_SC, 0);
    epoch = lds32(sb+OFF_MISC);
    const uint32_t par = epoch&1;
    auto ldx=[&](int w, int it){
      const uint32_t fb = bar+8*(B_XFULL+w*NX+(it&3));
      mbar_expect_tx(fb, XSLOT);
      tma2d_mc(sb+OFF_X+(w*NX+(it&3))*XSLOT+rank*4096, &maps.ht, w*1024+rt*64, ((it+(rt>>1)+w*(SKW/2))&7)*64+rank*32, fb);
    };
    if(warp!=9){
      const int cp = lane&3;
      uint32_t sw[4];
      { const uint4 w = shw;
        sw[0]=__byte_perm(w.x,w.z,0x5410); sw[1]=__byte_perm(w.x,w.z,0x7632); sw[2]=__byte_perm(w.y,w.w,0x5410); sw[3]=__byte_perm(w.y,w.w,0x7632); }
      const uint32_t udst = mapa(sb+OFF_U+(cp&1)*2*UCH, cp>>1), ubar = mapa(bar+8*B_U, cp>>1);
      asm volatile("barrier.cluster.wait.aligned;":::"memory");
      #pragma unroll 1
      for(int tk=(warp==8? 2:warp-10); tk<16; tk+=3){
        const int T=tk>>1, gl=(tk&1)*8+(lane>>2);
        mbar_wait(bar+8*(B_KV+T), 0);
        if(!(tk&1)) STAMP(8+T);
        const uint32_t ka = sb+KVOFF(T)+gl*16+cp*4, va = ka+2176;
        uint32_t kk[11], u[8];
        #pragma unroll
        for(int r=0;r<3;r++) kk[r]=lds32(ka+(5+r)*272);
        #pragma unroll
        for(int r=0;r<8;r++){ kk[3+r]=lds32(ka+16+r*272); u[r]=lds32(va+r*256); }
        #pragma unroll
        for(int r=0;r<8;r++){
          uint32_t a=hmul2_bf16(kk[r],sw[3]); a=hadd2_bf16(a,hmul2_bf16(kk[r+1],sw[2])); a=hadd2_bf16(a,hmul2_bf16(kk[r+2],sw[1])); a=hadd2_bf16(a,hmul2_bf16(kk[r+3],sw[0]));
          u[r]=hmul2_bf16(a,u[r]);
        }
        const int R = 255-(T*32+rank*16+gl);
        const uint32_t d = udst + (R&1)*UPL + (R>>1)*16;
        st_async128(d,     __byte_perm(u[7],u[6],0x5410), __byte_perm(u[5],u[4],0x5410), __byte_perm(u[3],u[2],0x5410), __byte_perm(u[1],u[0],0x5410), ubar+8*T);
        st_async128(d+UCH, __byte_perm(u[7],u[6],0x7632), __byte_perm(u[5],u[4],0x7632), __byte_perm(u[3],u[2],0x7632), __byte_perm(u[1],u[0],0x7632), ubar+8*T);
      }
      __syncwarp();
      if(lane==0) mbar_arrive(bar+8*B_TD);
    } else {
      asm volatile("barrier.cluster.wait.aligned;":::"memory");
    }
    if(warp==8){
      if(elect_one()){
        const int col = f*FS;
        #pragma unroll
        for(int it=W9; it<NS; it++){
          mbar_wait(bar+8*(B_WEMPTY+it), 0);
          if(it==4) mbar_wait(bar+8*B_TD, 0);
          if(it==5) mbar_wait(bar+8*(B_HD+1), 0);
          if(it>=PACE) mbar_wait(bar+8*(B_WFULL+it-PACE), 0);
          mbar_expect_tx(bar+8*(B_WFULL+it), 22528);
          load_w_stage(maps, sb+OFF_W+(5-it)*WSLOT, col, ((it+(rt&14))&15)*32, bar+8*(B_WFULL+it));
          if(it<5) STAMP(24+it);
        }
        mbar_wait(bar+8*(B_INIT+1), 0);
        mbar_wait(bar+8*B_X03, 0); ldx(0,3);
        uint32_t wb = bar, dst = sb+OFF_W+5*WSLOT, ph = 1; int k0 = ((6+(rt&14))&15)*32;
        #pragma unroll 1
        for(int j=4; j<4+(10+SKW)/2; j++){
          mbar_wait(wb+8*B_WEMPTY, ph);
          mbar_expect_tx(wb, 22528);       load_w_stage(maps, dst, col, k0, wb);
          mbar_wait(wb+8*B_WEMPTY+8, ph);
          mbar_expect_tx(wb+8, 22528);     load_w_stage(maps, dst-WSLOT, col, k0+32, wb+8);
          if(j<8){ mbar_wait(bar+8*(B_XEMPTY+(j&3)), 0); ldx(0,j); }
          const int j1 = j-SKW/2;
          if(j1>=4 && j1<8){ if(j1==4) mbar_wait(bar+8*(B_FB+1), 0); mbar_wait(bar+8*(B_XEMPTY+NX+(j1&3)), 0); ldx(1,j1); }
          if(j==5) asm volatile("cp.async.bulk.prefetch.L2.global [%0], 11008;"::"l"(wdn+b*5504):"memory");
          const bool wrap = wb==bar+32;
          wb = wrap? bar : wb+16; dst = wrap? dst+4*WSLOT : dst-2*WSLOT; ph ^= wrap; k0 = (k0+64)&511;
        }
        #pragma unroll
        for(int j=0;j<8;j++){
          constexpr int I0=16+SKW;
          const int slot=(I0+j)%NS, ci=(G2_CH>>(4*j))&3, kh=((G2_PEER>>j)&1)^rank;
          mbar_wait(bar+8*(B_WEMPTY+slot), ((I0+j)/NS)&1);
          mbar_expect_tx(bar+8*(B_WFULL+slot), 22528);
          tma2d(sb+OFF_W+(5-slot)*WSLOT, &maps.wd, rank*256+((fp+ci)&3)*64, (2*fp+kh)*FS, bar+8*(B_WFULL+slot));
        }
      }
      __syncwarp();
    } else if(warp==11){
      if(elect_one()){
        #pragma unroll 1
        for(int w=0;w<2;w++){ first_x(maps, sb, w); STAMP(w? 94:63); }
        mbar_arrive(bar+8*(B_INIT+1));
      }
      __syncwarp();
      __nanosleep(CSLEEP);
      STAMP(31);
      {
        const int j = rt*6+(lane>>2);
        float4 c = make_float4(0.f,0.f,0.f,0.f);
        if(lane<24 && j<88) c = gather_sum(&g_csp[(f*16+(lane&3)*4)*88+j], 4, 88, par);
        __syncwarp();
        #pragma unroll
        for(int o=1;o<4;o<<=1){ c.x+=__shfl_xor_sync(~0u,c.x,o); c.y+=__shfl_xor_sync(~0u,c.y,o); c.z+=__shfl_xor_sync(~0u,c.z,o); c.w+=__shfl_xor_sync(~0u,c.w,o); }
        if(lane<24 && j<88 && !(lane&3)) st_rlx128(&g_cs2[f*96+j], (__float_as_uint(c.x)&~1u)|par, __float_as_uint(c.y), __float_as_uint(c.z), __float_as_uint(c.w));
      }
      STAMP(29);
      { uint4 v[3]; int n=0; const int j2 = lane<24? lane+64 : lane;
        do{ __nanosleep(CSLEEP); ld_rlx128(&g_cs2[f*96+lane], v[0]); ld_rlx128(&g_cs2[f*96+lane+32], v[1]); ld_rlx128(&g_cs2[f*96+j2], v[2]); spin_guard(++n); }while(((v[0].x^par)|(v[1].x^par)|(v[2].x^par))&1);
        *(uint4*)(smem_raw+OFF_CS+lane*16)=v[0]; *(uint4*)(smem_raw+OFF_CS+(lane+32)*16)=v[1]; *(uint4*)(smem_raw+OFF_CS+j2*16)=v[2]; }
      mbar_wait(bar+8*(B_FB+1), 0);
      __syncwarp();
      if(lane<2) mbar_arrive(bar+8*(B_PAR+lane));
      STAMP(74);
      #pragma unroll 4
      for(int i=0;i<32;i++) g_xa[cb*1024+i*32+lane]=make_uint4(0,0,0,0);
    } else {
      const int w = warp-9;
      mbar_wait(bar+8*(B_HD+w), 0);
      STAMP(67+w*3);
      if(elect_one()){
        const unsigned tgt = lds32(sb+OFF_TGT+4+4*w);
        signal_add(&g_cnt[32+32*w]); STAMP(68+w*3);
        unsigned v; int n=0; do{ asm volatile("ld.acquire.gpu.global.u32 %0, [%1];":"=r"(v):"l"(&g_cnt[32+32*w]):"memory"); spin_guard(++n); }while((int)(v-tgt)<0);
        STAMP(7+w*16);
        asm volatile("fence.proxy.async.global;":::"memory");
        if(w) ldx(1,3); else mbar_arrive(bar+8*B_X03);
        mbar_arrive(bar+8*(B_FB+w));
      }
      __syncwarp();
      mbar_wait(bar+8*(B_RT+w), 0);
      {
        __nanosleep(CSLEEP);
        const float4 st=gather_sum(&g_stat[((rt*2+w)*8)*32+lane], 8, 32, par);
        const float s0=st.x, q0=st.y, s1=st.z, q1=st.w;
        const float m0=s0*(1.f/512), m1=s1*(1.f/512);
        const float v0=fmaxf(q0*(1.f/512)-m0*m0,0.f), v1=fmaxf(q1*(1.f/512)-m1*m1,0.f);
        const float r0=ln_rstd(v0), r1=ln_rstd(v1);
        *(float4*)(smem_raw+OFF_ROW+w*512+lane*16)=make_float4(-rbf(m0),r0,-rbf(m1),r1);
        mbar_wait(bar+8*(B_XEMPTY+w*NX+3), 0);
        __syncwarp();
        if(lane==0) mbar_arrive(bar+8*(B_PAR+w));
        STAMP(75+w);
      }
      if(elect_one()){
        const int orow = pos2row(w*1024+rt*64+53);
        #pragma unroll
        for(int c=0;c<HF;c++){
          mbar_wait(bar+8*(B_XEMPTY+w*NX+c), 1);
          tma4d_red_add(&maps.out8, rank*256+((fp+c)&3)*64, orow&7, (orow>>3)&15, orow>>7, sb+OFF_X+(w*NX+c)*XSLOT);
        }
        asm volatile("cp.async.bulk.commit_group;":::"memory");
        asm volatile("cp.async.bulk.wait_group.read 0;":::"memory");
        STAMP(77+w);
      }
      __syncwarp();
    }
  } else {
    if(elect_one()){
      mbar_init(bar+8*(B_Q+warp),1);
      asm volatile("fence.proxy.async.shared::cta;":::"memory");
      mbar_expect_tx(bar+8*(B_Q+warp), 2048);
      const bf16* qp = q + pos2row((1-wg)*1024+b*8+(warp&3)*2)*512;
      bulk_g2s(sb+OFF_Q+2*warp*QP, qp, 1024, bar+8*(B_Q+warp)); bulk_g2s(sb+OFF_Q+(2*warp+1)*QP, qp-16*512, 1024, bar+8*(B_Q+warp));
    }
    __syncwarp();
    asm volatile("setmaxnreg.inc.sync.aligned.u32 224;");
    if(elect_one()){
      mbar_init(bar+8*(B_U+warp),1); mbar_expect_tx(bar+8*(B_U+warp), 2048);
      mbar_init(bar+8*(B_XFULL+warp),1); mbar_init(bar+8*(B_XEMPTY+warp),8);
      mbar_init(bar+8*(B_KV+warp),1);
      if(warp<NS){ mbar_init(bar+8*(B_WFULL+warp),1); mbar_init(bar+8*(B_WEMPTY+warp),8); mbar_init(bar+8*(B_ONE+warp),1); }
      else { const int i=warp-6; mbar_init(bar+8*(B_PRDY+i),4); mbar_init(bar+8*(B_RT+i),1); mbar_init(bar+8*(B_AFULL+i),1); mbar_expect_tx(bar+8*(B_AFULL+i), 22528); mbar_init(bar+8*(B_PAR+i),2); mbar_init(bar+8*(B_HD+i),8+i); if(i){ mbar_init(bar+8*B_SC,1); mbar_init(bar+8*B_X03,1); } else { mbar_init(bar+8*B_QD,8); mbar_init(bar+8*B_TD,3); } }
      asm volatile("fence.mbarrier_init.release.cluster;":::"memory");
    }
    __syncwarp();
    STAMP(56);
    const int wq = warp&3, g = lane>>2, t = lane&3;
    if(tid<8){ sts128(sb+OFF_U+tid*UPL+128*16, 0,0,0,0); }
    if(tid<128) sts128(sb+OFF_ZB+tid*16, 0,0,0,0);
    if(tid<12){ sts128(sb+OFF_TBL+(tid&3)*TBL+(tid>>2)*16, 0,0,0,0); }
    uint4 kq[4]; uint32_t kn[4];
    #pragma unroll
    for(int i=0;i<4;i++){ kq[i]=ldg_nc128(ssmk+(b*4+i)*2048+tid*8); kn[i]=0; if(lane==31 && warp<7) asm volatile("ld.global.nc.u32 %0, [%1];":"=r"(kn[i]):"l"(ssmk+(b*4+i)*2048+tid*8+8)); }
    asm volatile("bar.sync 0;":::"memory");
    asm volatile("barrier.cluster.arrive.relaxed.aligned;":::"memory");
    STAMP(57);
    #pragma unroll
    for(int i=0;i<4;i++) mbar_wait(bar+8*(B_Q+wg*4+i), 0);
    STAMP(92+wg);
    {
      const uint32_t la = sb+OFF_Q+(wg*8+2*(lane>>3)+(lane&1))*QP + ((lane&7)>>1)*16 + wq*256;
      uint4 tv[4];
      const int irow = wq*32+t*2+(g>>2);
      const uint32_t dst = sb+OFF_IMG+irow*128+(((((g&3)+4*wg)^(b&7))^(irow&7))<<4);
      #pragma unroll
      for(int i=0;i<4;i++) ldsm4t(la+i*64, tv[i].x,tv[i].y,tv[i].z,tv[i].w);
      #pragma unroll
      for(int i=0;i<4;i++) sts128(dst+i*1024, max(~tv[i].x,1u),tv[i].y,tv[i].z,tv[i].w);
      asm volatile("fence.proxy.async.shared::cta;":::"memory");
      __syncwarp();
      if(lane==0) mbar_arrive(bar+8*B_QD);
      if(wg==0) STAMP(44);
    }
    {
      uint32_t w[2][8];
      const uint32_t qa = sb+OFF_Q+(2*warp)*QP+lane*16;
      #pragma unroll
      for(int r=0;r<2;r++){ lds128_nm(qa+r*QP, w[r][0],w[r][1],w[r][2],w[r][3]); lds128_nm(qa+r*QP+512, w[r][4],w[r][5],w[r][6],w[r][7]); }
      float s[2], d[2];
      #pragma unroll
      for(int r=0;r<2;r++){
        float s0=0.f,s1=0.f,d0=0.f,d1=0.f;
        #pragma unroll
        for(int i=0;i<8;i++){ const float lo=bf_lo(w[r][i]), hi=bf_hi(w[r][i]); s0+=lo; s1+=hi; d0=fmaf(lo,lo,d0); d1=fmaf(hi,hi,d1); }
        s[r]=s0+s1; d[r]=d0+d1;
      }
      const bool u=lane&16, v=lane&8;
      const float a0=(u? s[1]:s[0])+__shfl_xor_sync(~0u,u? s[0]:s[1],16), a1=(u? d[1]:d[0])+__shfl_xor_sync(~0u,u? d[0]:d[1],16);
      float c0=(v? a1:a0)+__shfl_xor_sync(~0u,v? a0:a1,8);
      c0+=__shfl_xor_sync(~0u,c0,4); c0+=__shfl_xor_sync(~0u,c0,2); c0+=__shfl_xor_sync(~0u,c0,1);
      const float m=c0*(1.f/512), sq=__shfl_down_sync(~0u,c0,8);
      const float rs=ln_rstd(fmaxf(fmaf(-m,m,sq*(1.f/512)),0.f)), rh=rbf(rs);
      const float m1=__shfl_down_sync(~0u,m,16), rs1=__shfl_down_sync(~0u,rs,16), rh1=rbf(rs1);
      mbar_wait(bar+8*B_SC, 0);
      if(lane==0){ st_rlx128(&g_qs[b*8+(warp^(b&7))], pack_bf16(m,m1), pack_bf16(rh,rh1), pack_bf16(rs-rh,rs1-rh1), lds32(sb+OFF_MISC)); }
      __syncwarp();
      if(wg==0) STAMP(46);
    }
    mbar_wait(bar+8*B_SC, 0);
    STAMP(90+wg);
    {
      const int Q = tid+2;
      const uint32_t ta = sb+OFF_TBL+((Q*32)^(((Q>>2)&3)<<5));
      const bool sw2 = (Q>>2)&1;
      if(tid==0){
        const uint32_t d01=lds32(sb+OFF_MISC+4), d23=lds32(sb+OFF_MISC+8);
        kq[0].x=hadd2_bf16(kq[0].x,d01&0xffffu); kq[1].x=hadd2_bf16(kq[1].x,d01>>16); kq[2].x=hadd2_bf16(kq[2].x,d23&0xffffu); kq[3].x=hadd2_bf16(kq[3].x,d23>>16);
      }
      __syncwarp();
      #pragma unroll
      for(int i=0;i<4;i++){
        uint32_t nx = __shfl_down_sync(~0u, kq[i].x, 1); if(lane==31) nx = kn[i];
        const uint4 o = make_uint4(__byte_perm(kq[i].x,kq[i].y,0x5432), __byte_perm(kq[i].y,kq[i].z,0x5432), __byte_perm(kq[i].z,kq[i].w,0x5432), __byte_perm(kq[i].w,nx,0x5432));
        const uint4 f0 = sw2? o:kq[i], f1 = sw2? kq[i]:o;
        sts128(ta+i*TBL+(sw2?16:0), f0.x,f0.y,f0.z,f0.w);
        sts128(ta+i*TBL+(sw2?0:16), f1.x,f1.y,f1.z,f1.w);
        if(tid==0) sts128(sb+OFF_TBL+i*TBL+48, 0,0,0, kq[i].x<<16);
      }
      __syncwarp();
      asm volatile("bar.sync 1, 256;":::"memory");
    }
    __syncwarp();
    if(lane<3) mbar_arrive(bar+8*(B_WEMPTY+(lane==2? 4:lane)));
    STAMP(80+wg);
    STAMP(82+wg);
    asm volatile("barrier.cluster.wait.aligned;":::"memory");
    bool x_ok = false;
    {
      const int c=lane>>3, p=g&1;
      uint32_t tb[5];
      #pragma unroll
      for(int s=0;s<5;s++){ const int y=16*c+wq+t+p+4*s; const int id=8*(y>>2)+4*(1-p)+(y&3); tb[s]=sb+OFF_TBL+wg*2*TBL+((id^(((id>>5)&3)<<3))<<2); }
      uint64_t du = make_desc(sb+OFF_U+wg*2*UCH, UPL, 128, 0);
      float aE[2][32], aL[2][32];
      uint32_t R[2][4][8], oku=0; uint4 xr[4], st[8], ar[2], e0;
#define P_TY(K) ((K)>=8 ? 2 : (K)&1)
#define P_LV(K) ((K)>=8 ? (K)-8 : (K)>>1)
#define P_MA(K) ((P_TY(K)==1 ? 15 : 7) - 2*P_LV(K))
#define P_N(K,M) (P_TY(K)==2 ? 64 : P_TY(K)==1 ? 128-8*(M) : 64-8*(M))
#define P_B(K,M) (8*(M) + (P_TY(K)==0 ? 64 : 0))
#define P_LD(K,J) conv_lda(R[(K)&1][J],tb,((J)&1)*TBL+(P_MA(K)-((J)>>1))*512)
#define P_MMA(K,J) conv_mma<P_N(K,P_MA(K)-((J)>>1))>(P_TY(K)==0? aE[(J)&1]:aL[(J)&1], R[(K)&1][J], du+((J)&1)*(UCH/16)+P_B(K,P_MA(K)-((J)>>1)))
#define CONV_PREP(K) { if constexpr(P_TY(K)!=1) oku = mbar_test(bar+8*(B_U+P_LV(K)+(P_TY(K)?4:0)),0); P_LD(K,0); P_LD(K,1); P_LD(K,2); P_LD(K,3); }
#define CONV_PAIR(K) { \
        _Pragma("unroll") for(int j=0;j<4;j++) conv_dup(R[(K)&1][j]); \
        if constexpr(P_TY(K)<2){ _Pragma("unroll") for(int i=0;i<2;i++){ float* a_=(P_TY(K)==0? aE[i]:aL[i])+8*P_LV(K); zero4(a_); zero4(a_+4); } } \
        if constexpr(P_TY(K)!=1){ if(!oku) mbar_wait(bar+8*(B_U+P_LV(K)+(P_TY(K)?4:0)),0); asm volatile("fence.proxy.async.shared::cta;":::"memory"); } \
        asm volatile("" : "+l"(du)); \
        PP_SYNC(); \
        if constexpr((K)==0||(K)==6||(K)==7||(K)==11){ if(wg==0) STAMP(96+(K)); } \
        wg_fence(); \
        P_MMA(K,0); P_MMA(K,1); \
        if constexpr(P_TY(K)<2){ wg_commit(); wg_fence(); } \
        P_MMA(K,2); P_MMA(K,3); \
        wg_commit(); \
        if((K)<11 || wg==0) PP_ARRIVE(); \
        if constexpr((K)<11){ if constexpr((K)>0){ if constexpr(P_TY(K)<2) wg_wait<2>(); else wg_wait<1>(); } if constexpr((K)!=6 && (K)!=0) CONV_PREP((K)+1) } }
#define PP_SYNC() asm volatile("bar.sync %0, 256;"::"r"(2+wg):"memory")
#define PP_ARRIVE() asm volatile("bar.arrive %0, 256;"::"r"(3-wg):"memory")
      if(wg==1) PP_ARRIVE();
      CONV_PREP(0) CONV_PREP(1) CONV_PAIR(0) CONV_PAIR(1) CONV_PAIR(2) CONV_PAIR(3) CONV_PAIR(4) CONV_PAIR(5)
      mbar_wait(bar+8*B_XA,0);
      wg_wait<0>();
      load_xs(xr,st,sb,warp,lane); check_xs(xr,st,lds32(sb+OFF_MISC),sb,warp); ln_x(xr+2,st+4,ar);
      if(lane==0) mbar_arrive(bar+8*(B_WEMPTY+3));
      CONV_PAIR(6)
      if(lane==0) mbar_arrive(bar+8*(B_WEMPTY+2));
      wg_wait<0>();
      conv_put<1>(aE[0],aE[1],e0,sb,warp,lane);
      CONV_PREP(7)
      conv_get<1>(xr+2,ar,sb,warp,lane);
      __syncwarp();
      if(lane==0) mbar_arrive(bar+8*B_HD);
      STAMP(84+wg);
      CONV_PAIR(7) CONV_PAIR(8) CONV_PAIR(9) CONV_PAIR(10) CONV_PAIR(11)
      ln_x(xr,st,ar);
      if(wg==0 && mbar_test(bar+8*B_XFULL, 0)) x_ok = !x_bad(sb, 0, wq, lane);
      wg_wait<0>();
      STAMP(86+wg);
      conv_put<0>(aL[0],aL[1],e0,sb,warp,lane);
      conv_get<0>(xr,ar,sb,warp,lane);
      __syncwarp();
      if(lane==0){ mbar_arrive(bar+8*(B_HD+1)); mbar_arrive(bar+8*(B_WEMPTY+5)); }
      STAMP(88+wg);
    }
    if(wg==1 && wq<3){
      mbar_wait(bar+8*(B_WFULL+SKW+(rt&1)), 0);
      const int j = tid-128;
      const uint32_t par = lds32(sb+OFF_MISC)&1;
      float c0=0.f,c1=0.f,c2=0.f,c3=0.f;
      const uint32_t cb = sb+OFF_W+(5-SKW-(rt&1))*WSLOT+wq*8192+t*4+maps.upfirst*4096;
      #pragma unroll CSU
      for(int k=0;k<32;k++){
        const uint32_t ad = cb + k*128 + ((g^(k&7))<<4);
        const uint32_t v=lds32(ad), u=lds32(ad+4096-maps.upfirst*8192); c0+=bf_lo(v); c1+=bf_hi(v); c2+=bf_lo(u); c3+=bf_hi(u);
      }
      if(j<88) st_rlx128(&g_csp[(f*16+rt)*88+j], (__float_as_uint(c0)&~1u)|par, __float_as_uint(c1), __float_as_uint(c2), __float_as_uint(c3));
      __syncwarp();
      STAMP(73);
    }
    const uint32_t xempty_cl = mapa(bar+8*(B_XEMPTY+wg*NX), lane&1);
    float ag[88], au[88];
    const uint32_t xbase = sb+OFF_X+wg*NX*XSLOT, rbase = sb+(wg? OFF_RES1:OFF_RES0);
    const uint32_t rfrag = rbase+((lane&7)+8*(lane>>4))*128+(((2*wq+((lane>>3)&1))^(lane&7))<<4);
    constexpr uint64_t DHI_A = (uint64_t)0x40000040u<<32, DHI_B = DHI_A | (512u<<16);
    const uint32_t og = maps.upfirst*256, ou = 256-og;
    uint32_t wb = bar+8*wg*(SKW%NS), ph = wg*(SKW/NS), dbl = (((sb+OFF_W+(5-wg*(SKW%NS))*WSLOT)&0x3FFFF)>>4), dal = (xbase&0x3FFFF)>>4, xb = bar+8*(B_XFULL+wg*NX), pwb = 0;
    uint32_t relm = lane==0? 0xff : lane==1? (wg? (0xff00>>(SKW/2))&0xff : (1<<(SKW/2))-1) : 0;
#define G1_STAGE(DA,DB,ACC) { wg_fence(); wgmma_ss<176,1,1>(ag, DA, DHI_B|((DB)+og), ACC); wgmma_ss<176,1,1>(au, DA, DHI_B|((DB)+ou), ACC); wgmma_ss<176,1,1>(ag, (DA)+128, DHI_B|((DB)+og+128), 1); wgmma_ss<176,1,1>(au, (DA)+128, DHI_B|((DB)+ou+128), 1); wg_commit(); }
    {
      mbar_wait(wb, ph);
      if(!x_ok){
        mbar_wait(xb, 0);
        STAMP(wg? 47:45);
        if(x_bad(sb, wg, wq, lane)){
          const uint32_t par = lds32(sb+OFF_MISC), co = lane*128+(((2*wq)^(lane&7))<<4);
          #pragma unroll 1
          for(int tl=0;tl<4;tl++){
            const bf16* src = g_hT+((tl<3? ((rt>>1)+wg*(SKW/2)+tl)&7 : rank*4+fp)*64+lane)*2048+wg*1024+rt*64+wq*16;
            uint4 v[4]; int n=0;
            do{
              #pragma unroll
              for(int i=0;i<4;i++) ld_rlx128(src+(i>>1)*32*2048+(i&1)*8, v[i]);
            }while((((v[0].x^par)|(v[1].x^par)|(v[2].x^par)|(v[3].x^par))&1) && ++n<2000000);
            #pragma unroll
            for(int i=0;i<4;i++) sts128(((tl<3? xbase+tl*8192 : rbase)+(i>>1)*4096+co)^((i&1)<<4), v[i].x,v[i].y,v[i].z,v[i].w);
          }
          asm volatile("fence.proxy.async.shared::cta;":::"memory");
          __syncwarp();
        }
      }
      STAMP(1+wg*16);
      #pragma unroll
      for(int i=0;i<88;i++){ ag[i]=0.f; au[i]=0.f; }
      G1_STAGE(DHI_A|dal, dbl, 0)
    }
    uint32_t okb = mbar_test(wb+8, ph);
    #pragma unroll 1
    for(int xi=0; xi<8; xi++){
      if(!okb) mbar_wait(wb+8, ph);
      G1_STAGE(DHI_A|(dal+256), dbl-WSLOT/16, 1)
      pwb = wb;
      const bool wrap = wb==bar+8*4;
      wb = wrap? bar : wb+16; dbl = wrap? dbl+4*(WSLOT/16) : dbl-2*(WSLOT/16); ph ^= wrap;
      dal = (xi==3)? dal-3*512 : dal+512; xb = (xi==3)? xb-24 : xb+8;
      const uint32_t oka = mbar_test(xb, xi>=3) & mbar_test(wb, ph);
      if(xi==(wg? STX1:STX0)){
        float s0=0.f,s1=0.f,q0=0.f,q1=0.f;
        #pragma unroll
        for(int kk=0;kk<4;kk++){
          uint32_t r[4]; ldsm4t(rfrag+kk*2048, r[0],r[1],r[2],r[3]);
          #pragma unroll
          for(int i=0;i<4;i++){ const float lo=bf_lo(r[i]), hi=bf_hi(r[i]); if(i&1){ s1+=lo+hi; q1=fmaf(lo,lo,fmaf(hi,hi,q1)); } else { s0+=lo+hi; q0=fmaf(lo,lo,fmaf(hi,hi,q0)); } }
        }
        #pragma unroll
        for(int o=1;o<4;o<<=1){ s0+=__shfl_xor_sync(~0u,s0,o); q0+=__shfl_xor_sync(~0u,q0,o); s1+=__shfl_xor_sync(~0u,s1,o); q1+=__shfl_xor_sync(~0u,q1,o); }
        if(t==0) st_rlx128(&g_stat[((rt*2+wg)*8+f)*32+wq*8+g], (__float_as_uint(s0)&~1u)|(lds32(sb+OFF_MISC)&1), __float_as_uint(q0), __float_as_uint(s1), __float_as_uint(q1));
        __syncwarp();
        if(tid==wg*128) mbar_arrive(bar+8*(B_RT+wg));
      }
      uint32_t rel = relm&1; relm>>=1; uint32_t xpar = xi>=3;
      asm volatile("":"+r"(rel),"+r"(xpar));
      wg_wait<1>();
      if(rel) mbar_arrive(pwb+8*B_WEMPTY);
      if(xi==7) break;
      if(!oka){ mbar_wait(xb, xpar); mbar_wait(wb, ph); }
      G1_STAGE(DHI_A|dal, dbl, 1)
      okb = mbar_test(wb+8, ph);
      wg_wait<1>();
      if(rel) mbar_arrive(pwb+8*B_WEMPTY+8);
      if((lane>>1)==1 && xi<4) mbar_arrive_cl(xempty_cl+8*xi);
      if(xi==6 && lane==0) mbar_arrive_cl(mapa(bar+8*(B_PRDY+wg), rank^1));
    }
    mbar_wait(bar+8*(B_PAR+wg), 0);
    mbar_wait(bar+8*(B_PRDY+wg), 0);
    const float4 p0=*(const float4*)(smem_raw+OFF_ROW+(wg*32+wq*8+g)*16);
    const float nm0=p0.x, r0=p0.y, nm1=p0.z, r1=p0.w;
    wg_wait<0>();
    STAMP(2+wg*16);
    if(lane==0){ mbar_arrive_n(pwb+8*B_WEMPTY+8, (wg && SKW)? 2:1); }
    uint32_t act[44], actp[44];
    const float sc0=0.5f*r0*r0, sc1=0.5f*r1*r1;
    const uint32_t adst = mapa(xbase+(3-wq)*2048+lane*16, rank^1), abar = mapa(bar+8*(B_AFULL+wg), rank^1);
    {
      const float4* cs = (const float4*)(smem_raw+OFF_CS);
      const float h0=0.5f*r0, h1=0.5f*r1;
      #pragma unroll
      for(int j=0;j<22;j++){
        const float4 c4=cs[4*j+t];
        const float g0=fmaf(nm0,c4.x,ag[4*j+0]), g1=fmaf(nm0,c4.y,ag[4*j+1]), g2=fmaf(nm1,c4.x,ag[4*j+2]), g3=fmaf(nm1,c4.y,ag[4*j+3]);
        const float y0=g0*fmaf(nm0,c4.z,au[4*j+0]), y1=g1*fmaf(nm0,c4.w,au[4*j+1]), y2=g2*fmaf(nm1,c4.z,au[4*j+2]), y3=g3*fmaf(nm1,c4.w,au[4*j+3]);
        act[2*j]  =pack_bf16(y0*fmaf(sc0,tanh_fast(g0*h0),sc0), y1*fmaf(sc0,tanh_fast(g1*h0),sc0));
        act[2*j+1]=pack_bf16(y2*fmaf(sc1,tanh_fast(g2*h1),sc1), y3*fmaf(sc1,tanh_fast(g3*h1),sc1));
        if((j%3)==2 && j/3<NIN){ const int kk=j/3; st_async128(adst+(kk>>2)*8192+(kk&3)*512, act[4*kk],act[4*kk+1],act[4*kk+2],act[4*kk+3], abar); }
      }
    }
    STAMP(3+wg*16);
    #pragma unroll
    for(int kk=NIN;kk<11;kk++) st_async128(adst+(kk>>2)*8192+(kk&3)*512, act[4*kk],act[4*kk+1],act[4*kk+2],act[4*kk+3], abar);
    float acc2[2][32];
    #pragma unroll
    for(int i=0;i<32;i++){ acc2[0][i]=0.f; acc2[1][i]=0.f; }
    const uint32_t wbase = xbase+(3-wq)*2048;
    const uint32_t srow = ((~lane&4)<<1) | ((~lane&1)<<2) | (lane&2) | ((lane>>3)&1);
    const int orow = pos2row(wg*1024+rt*64+wq*16+5);
    uint32_t hr[16];
    #pragma unroll
    for(int kk=0;kk<4;kk++) ldsm4t(rfrag+kk*2048, hr[4*kk],hr[4*kk+1],hr[4*kk+2],hr[4*kk+3]);
    auto stage=[&](const float* a, int c){
      #pragma unroll
      for(int kk=0;kk<4;kk++){
        uint32_t o0=pack_bf16(a[8*kk],a[8*kk+1]), o1=pack_bf16(a[8*kk+2],a[8*kk+3]), o2=pack_bf16(a[8*kk+4],a[8*kk+5]), o3=pack_bf16(a[8*kk+6],a[8*kk+7]);
        if(c==0){
          o0=hadd2_bf16(o0,hr[4*kk]); o1=hadd2_bf16(o1,hr[4*kk+1]); o2=hadd2_bf16(o2,hr[4*kk+2]); o3=hadd2_bf16(o3,hr[4*kk+3]);
        }
        stsm4_nm(wbase+c*8192+srow*128+(((2*kk+(lane>>4))^(srow&7))<<4), o0,o1,o2,o3);
      }
    };
    auto flush=[&](int c, int n){
      asm volatile("fence.proxy.async.shared::cta;":::"memory");
      __syncwarp();
      if(c<HF){ if(lane<2) mbar_arrive(bar+8*(B_XEMPTY+wg*NX+c)); }
      else if(elect_one()){
        tma4d_red_add(&maps.out, rank*256+((fp+c)&3)*64, orow&7, (orow>>3)&15, orow>>7, wbase+c*8192);
        asm volatile("cp.async.bulk.commit_group;":::"memory");
      }
    };
    uint32_t okw = 0;
    #pragma unroll
    for(int i=0;i<8;i++){
      const int ch = (G2_CH>>(4*i))&3, peer = (G2_PEER>>i)&1;
      constexpr int S0=(16+SKW)%NS, P0=((16+SKW)/NS)&1;
      const int slot=(S0+i)%NS, pslot=(S0+i+NS-1)%NS, ph=(P0+(S0+i)/NS)&1;
      if(i==2){
        mbar_wait(bar+8*(B_AFULL+wg), 0);
        #pragma unroll
        for(int kk=0;kk<11;kk++) lds128_nm(wbase+lane*16+(kk>>2)*8192+(kk&3)*512, actp[4*kk],actp[4*kk+1],actp[4*kk+2],actp[4*kk+3]);
      }
      if(!okw) mbar_wait(bar+8*(B_WFULL+slot), ph);
      if(i<7) okw = mbar_test(bar+8*(B_WFULL+(S0+i+1)%NS), (P0+(S0+i+1)/NS)&1);
      if(i==2 || i==4 || i==6 || (i==0 && wg==1)) asm volatile("bar.sync %0, 256;"::"r"(2+wg):"memory");
      const uint64_t db = make_desc(sb+OFF_W+(5-slot)*WSLOT, 0, 1024, 1);
      wg_fence();
      #pragma unroll
      for(int kk=0;kk<11;kk++){
        if(peer) wgmma_rs<64,1>(acc2[ch&1], actp[4*kk],actp[4*kk+1],actp[4*kk+2],actp[4*kk+3], db+kk*128, 1);
        else     wgmma_rs<64,1>(acc2[ch&1], act[4*kk],act[4*kk+1],act[4*kk+2],act[4*kk+3], db+kk*128, kk>0);
      }
      wg_commit();
      if(i==1 || i==3 || i==5 || (i==7 && wg==0)) asm volatile("bar.arrive %0, 256;"::"r"(3-wg):"memory");
      if(i==1){ wg_wait<0>(); if(lane<2) mbar_arrive(bar+8*(B_WEMPTY+(lane? slot:pslot))); }
      if(i==3){ wg_wait<1>(); stage(acc2[0], 0); flush(0,1); wg_wait<0>(); stage(acc2[1], 1); flush(1,1); }
      if(i==5){ wg_wait<0>(); stage(acc2[0], 2); flush(2,1); }
      STAMP(32+wg*16+i);
    }
    wg_wait<0>();
    STAMP(4+wg*16);
    stage(acc2[1], 3); flush(3,1);
    STAMP(5+wg*16);
    asm volatile("cp.async.bulk.wait_group.read 0;":::"memory");
    STAMP(6+wg*16);
  }
}

__device__ bf16 g_fb[S_*F_+2*S_*D_];
__device__ __forceinline__ float b2f_(bf16 x){ return __bfloat162float(x); }
__global__ void fb_ln(const bf16* x, bf16* y){
  __shared__ float red[16]; const int r=blockIdx.x, t=threadIdx.x; const float v=b2f_(x[r*512+t]);
  float s=v; for(int o=16;o;o>>=1) s+=__shfl_xor_sync(~0u,s,o); if((t&31)==0) red[t>>5]=s; __syncthreads(); s=0; for(int i=0;i<16;i++) s+=red[i]; const float m=s/512; __syncthreads();
  float d=(v-m)*(v-m); for(int o=16;o;o>>=1) d+=__shfl_xor_sync(~0u,d,o); if((t&31)==0) red[t>>5]=d; __syncthreads(); d=0; for(int i=0;i<16;i++) d+=red[i];
  y[r*512+t]=__float2bfloat16(rbf(v-rbf(m))/rbf(sqrtf(rbf(rbf(d/512)+1e-5f)))); }
__global__ void fb_kv(const bf16* k, const bf16* v, const bf16* sh, bf16* kv){ const int s=blockIdx.x, d=threadIdx.x; float a=0;
  for(int t=0;t<4;t++){ const int r=s+t-3; a=rbf(a+rbf((r>=0? b2f_(k[r*512+d]):0.f)*b2f_(sh[d*4+3-t]))); } kv[s*512+d]=__float2bfloat16(a*b2f_(v[s*512+d])); }
__global__ void fb_conv(const bf16* x, const bf16* qn, const bf16* kv, const bf16* K, const bf16* Dv, bf16* h){ const int s=blockIdx.x, d=threadIdx.x; float a=0;
  for(int j=0;j<=s;j++) a+=b2f_(K[d*2048+j])*b2f_(kv[(s-j)*512+d]);
  h[s*512+d]=__float2bfloat16(b2f_(x[s*512+d])+rbf(b2f_(qn[s*512+d])*rbf(rbf(a)+rbf(b2f_(kv[s*512+d])*b2f_(Dv[d]))))); }
__global__ void fb_g1(const bf16* xn, const bf16* wg, const bf16* wu, bf16* act){ const int s=blockIdx.x;
  for(int n=threadIdx.x;n<F_;n+=blockDim.x){ float g=0,u=0; for(int k=0;k<512;k++){ const float x=b2f_(xn[s*512+k]); g+=x*b2f_(wg[k*F_+n]); u+=x*b2f_(wu[k*F_+n]); }
    g=rbf(g); act[s*F_+n]=__float2bfloat16(rbf(g/(1.f+expf(-g)))*rbf(u)); } }
__global__ void fb_g2(const bf16* act, const bf16* wd, const bf16* h, bf16* out){ const int s=blockIdx.x, n=threadIdx.x; float a=0;
  for(int k=0;k<F_;k++) a+=b2f_(act[s*F_+k])*b2f_(wd[k*512+n]); out[s*512+n]=__float2bfloat16(b2f_(h[s*512+n])+rbf(a)); }

typedef CUresult (*PFN_encodeTiled)(CUtensorMap*, CUtensorMapDataType, cuuint32_t, void*, const cuuint64_t*, const cuuint64_t*, const cuuint32_t*, const cuuint32_t*, CUtensorMapInterleave, CUtensorMapSwizzle, CUtensorMapL2promotion, CUtensorMapFloatOOBfill);
static int g_enc_err;
static void make2d(PFN_encodeTiled enc, CUtensorMap* m, const void* p, uint64_t d0, uint64_t d1, uint32_t b0, uint32_t b1){
  cuuint64_t gd[2]={d0,d1}; cuuint64_t gs[1]={d0*2}; cuuint32_t bx[2]={b0,b1}; cuuint32_t es[2]={1,1};
  g_enc_err |= (int)enc(m,CU_TENSOR_MAP_DATA_TYPE_BFLOAT16,2,(void*)p,gd,gs,bx,es,CU_TENSOR_MAP_INTERLEAVE_NONE,CU_TENSOR_MAP_SWIZZLE_128B,CU_TENSOR_MAP_L2_PROMOTION_L2_128B,CU_TENSOR_MAP_FLOAT_OOB_FILL_NONE);
}
static void make3d(PFN_encodeTiled enc, CUtensorMap* m, const void* p, uint64_t d0, uint64_t d1, uint64_t d2, uint64_t s1, uint64_t s2, uint32_t b0, uint32_t b1, uint32_t b2, CUtensorMapSwizzle sw, CUtensorMapL2promotion pr){
  cuuint64_t gd[3]={d0,d1,d2}; cuuint64_t gs[2]={s1,s2}; cuuint32_t bx[3]={b0,b1,b2}; cuuint32_t es[3]={1,1,1};
  g_enc_err |= (int)enc(m,CU_TENSOR_MAP_DATA_TYPE_BFLOAT16,3,(void*)p,gd,gs,bx,es,CU_TENSOR_MAP_INTERLEAVE_NONE,sw,pr,CU_TENSOR_MAP_FLOAT_OOB_FILL_NONE);
}

extern "C" void kernel_launch(void* const* d_in, const int* in_sizes, int n_in, void* d_out, int out_size){
  const bf16* q=(const bf16*)d_in[0]; const bf16* k=(const bf16*)d_in[1]; const bf16* v=(const bf16*)d_in[2];
  const bf16* sh=(const bf16*)d_in[3]; const bf16* K=(const bf16*)d_in[4]; const bf16* Dv=(const bf16*)d_in[5];
  const bf16* wgt=(const bf16*)d_in[7]; const bf16* wup=(const bf16*)d_in[8]; const bf16* wdn=(const bf16*)d_in[9];
  void* fn=nullptr; cudaDriverEntryPointQueryResult qr; cudaGetDriverEntryPoint("cuTensorMapEncodeTiled",&fn,cudaEnableDefault,&qr);
  PFN_encodeTiled enc=(PFN_encodeTiled)fn;
  void* hT; cudaGetSymbolAddress(&hT,g_hT);
  Maps maps; g_enc_err = 0;
  make3d(enc,&maps.k,k,512,256,8,8192,1024,8,17,8,CU_TENSOR_MAP_SWIZZLE_NONE,CU_TENSOR_MAP_L2_PROMOTION_L2_128B);
  make3d(enc,&maps.v,v,512,256,8,8192,1024,8,16,8,CU_TENSOR_MAP_SWIZZLE_NONE,CU_TENSOR_MAP_L2_PROMOTION_L2_128B);
  { maps.upfirst = wup<wgt; const bf16* w0 = wup<wgt? wup:wgt; const uint64_t dm = (uint64_t)((wup<wgt? wgt-wup : wup-wgt)*2);
    cuuint64_t gd[4]={F_,D_,2,2}; cuuint64_t gs[3]={F_*2,dm,128}; cuuint32_t bx[4]={64,32,2,2}; cuuint32_t es[4]={1,1,1,1};
    g_enc_err |= (int)enc(&maps.w64,CU_TENSOR_MAP_DATA_TYPE_BFLOAT16,4,(void*)w0,gd,gs,bx,es,CU_TENSOR_MAP_INTERLEAVE_NONE,CU_TENSOR_MAP_SWIZZLE_128B,CU_TENSOR_MAP_L2_PROMOTION_L2_128B,CU_TENSOR_MAP_FLOAT_OOB_FILL_NONE);
    make3d(enc,&maps.w48,w0,F_,D_,2,F_*2,dm,48,32,2,CU_TENSOR_MAP_SWIZZLE_128B,CU_TENSOR_MAP_L2_PROMOTION_L2_128B); }
  make2d(enc,&maps.wd,wdn,D_,F_,64,176);
  make2d(enc,&maps.ht,hT,S_,D_,64,32);
  { cuuint64_t gd[4]={512,8,16,16}; cuuint64_t gs[3]={1024,8192,131072}; cuuint32_t bx[4]={64,2,4,2}; cuuint32_t es[4]={1,1,1,1};
    g_enc_err |= (int)enc(&maps.out,CU_TENSOR_MAP_DATA_TYPE_BFLOAT16,4,d_out,gd,gs,bx,es,CU_TENSOR_MAP_INTERLEAVE_NONE,CU_TENSOR_MAP_SWIZZLE_128B,CU_TENSOR_MAP_L2_PROMOTION_NONE,CU_TENSOR_MAP_FLOAT_OOB_FILL_NONE);
    bx[3]=8; g_enc_err |= (int)enc(&maps.out8,CU_TENSOR_MAP_DATA_TYPE_BFLOAT16,4,d_out,gd,gs,bx,es,CU_TENSOR_MAP_INTERLEAVE_NONE,CU_TENSOR_MAP_SWIZZLE_128B,CU_TENSOR_MAP_L2_PROMOTION_NONE,CU_TENSOR_MAP_FLOAT_OOB_FILL_NONE); }
  void* xa; cudaGetSymbolAddress(&xa,g_xa);
  make2d(enc,&maps.xa,xa,8192,128,64,128);
  cudaFuncSetAttribute(fused_kernel,cudaFuncAttributeMaxDynamicSharedMemorySize,SMEM_BYTES);
  int ncl = 0;
  { cudaLaunchConfig_t cfg = {}; cfg.gridDim = dim3(128); cfg.blockDim = dim3(384); cfg.dynamicSmemBytes = SMEM_BYTES;
    cudaLaunchAttribute at[1]; at[0].id = cudaLaunchAttributeClusterDimension; at[0].val.clusterDim.x = 2; at[0].val.clusterDim.y = 1; at[0].val.clusterDim.z = 1;
    cfg.attrs = at; cfg.numAttrs = 1;
    if(cudaOccupancyMaxActiveClusters(&ncl, fused_kernel, &cfg) != cudaSuccess){ ncl = 0; (void)cudaGetLastError(); } }
  if(FORCE_FB || g_enc_err || ncl < 64){
    bf16* fb; cudaGetSymbolAddress((void**)&fb, g_fb); bf16 *ln=fb, *kv=fb+S_*D_, *act=fb+2*S_*D_;
    fb_ln<<<S_,512>>>(q,ln); fb_kv<<<S_,512>>>(k,v,sh,kv); fb_conv<<<S_,512>>>(q,ln,kv,K,Dv,(bf16*)hT); fb_ln<<<S_,512>>>((bf16*)hT,ln);
    fb_g1<<<S_,256>>>(ln,wgt,wup,act); fb_g2<<<S_,512>>>(act,wdn,(bf16*)hT,(bf16*)d_out);
    return;
  }
  fused_kernel<<<128,384,SMEM_BYTES>>>(maps,q,sh,K,Dv,wdn,(bf16*)d_out);
}
```

```cpp
#include <cuda_runtime.h>
#include <cuda_bf16.h>
#include <cuda.h>
#include <stdint.h>

template<int TA,int TB> __device__ __forceinline__ void wgmma_ss_n176(float* d, uint64_t da, uint64_t db, int sd){
  asm volatile("{ .reg .pred p; setp.ne.b32 p, %90, 0; wgmma.mma_async.sync.aligned.m64n176k16.f32.bf16.bf16 {%0,%1,%2,%3,%4,%5,%6,%7,%8,%9,%10,%11,%12,%13,%14,%15,%16,%17,%18,%19,%20,%21,%22,%23,%24,%25,%26,%27,%28,%29,%30,%31,%32,%33,%34,%35,%36,%37,%38,%39,%40,%41,%42,%43,%44,%45,%46,%47,%48,%49,%50,%51,%52,%53,%54,%55,%56,%57,%58,%59,%60,%61,%62,%63,%64,%65,%66,%67,%68,%69,%70,%71,%72,%73,%74,%75,%76,%77,%78,%79,%80,%81,%82,%83,%84,%85,%86,%87}, %88, %89, p, 1, 1, %91, %92; }"
   : "+f"(d[0]),"+f"(d[1]),"+f"(d[2]),"+f"(d[3]),"+f"(d[4]),"+f"(d[5]),"+f"(d[6]),"+f"(d[7]),"+f"(d[8]),"+f"(d[9]),"+f"(d[10]),"+f"(d[11]),"+f"(d[12]),"+f"(d[13]),"+f"(d[14]),"+f"(d[15]),"+f"(d[16]),"+f"(d[17]),"+f"(d[18]),"+f"(d[19]),"+f"(d[20]),"+f"(d[21]),"+f"(d[22]),"+f"(d[23]),"+f"(d[24]),"+f"(d[25]),"+f"(d[26]),"+f"(d[27]),"+f"(d[28]),"+f"(d[29]),"+f"(d[30]),"+f"(d[31]),"+f"(d[32]),"+f"(d[33]),"+f"(d[34]),"+f"(d[35]),"+f"(d[36]),"+f"(d[37]),"+f"(d[38]),"+f"(d[39]),"+f"(d[40]),"+f"(d[41]),"+f"(d[42]),"+f"(d[43]),"+f"(d[44]),"+f"(d[45]),"+f"(d[46]),"+f"(d[47]),"+f"(d[48]),"+f"(d[49]),"+f"(d[50]),"+f"(d[51]),"+f"(d[52]),"+f"(d[53]),"+f"(d[54]),"+f"(d[55]),"+f"(d[56]),"+f"(d[57]),"+f"(d[58]),"+f"(d[59]),"+f"(d[60]),"+f"(d[61]),"+f"(d[62]),"+f"(d[63]),"+f"(d[64]),"+f"(d[65]),"+f"(d[66]),"+f"(d[67]),"+f"(d[68]),"+f"(d[69]),"+f"(d[70]),"+f"(d[71]),"+f"(d[72]),"+f"(d[73]),"+f"(d[74]),"+f"(d[75]),"+f"(d[76]),"+f"(d[77]),"+f"(d[78]),"+f"(d[79]),"+f"(d[80]),"+f"(d[81]),"+f"(d[82]),"+f"(d[83]),"+f"(d[84]),"+f"(d[85]),"+f"(d[86]),"+f"(d[87]) : "l"(da), "l"(db), "r"(sd), "n"(TA), "n"(TB));
}
template<int TB> __device__ __forceinline__ void wgmma_rs_n8(float* d, uint32_t a0, uint32_t a1, uint32_t a2, uint32_t a3, uint64_t db, int sd){
  asm volatile("{ .reg .pred p; setp.ne.b32 p, %9, 0; wgmma.mma_async.sync.aligned.m64n8k16.f32.bf16.bf16 {%0,%1,%2,%3}, {%4,%5,%6,%7}, %8, p, 1, 1, %10; }"
   : "+f"(d[0]),"+f"(d[1]),"+f"(d[2]),"+f"(d[3]) : "r"(a0),"r"(a1),"r"(a2),"r"(a3), "l"(db), "r"(sd), "n"(TB));
}
template<int TB> __device__ __forceinline__ void wgmma_rs_n16(float* d, uint32_t a0, uint32_t a1, uint32_t a2, uint32_t a3, uint64_t db, int sd){
  asm volatile("{ .reg .pred p; setp.ne.b32 p, %13, 0; wgmma.mma_async.sync.aligned.m64n16k16.f32.bf16.bf16 {%0,%1,%2,%3,%4,%5,%6,%7}, {%8,%9,%10,%11}, %12, p, 1, 1, %14; }"
   : "+f"(d[0]),"+f"(d[1]),"+f"(d[2]),"+f"(d[3]),"+f"(d[4]),"+f"(d[5]),"+f"(d[6]),"+f"(d[7]) : "r"(a0),"r"(a1),"r"(a2),"r"(a3), "l"(db), "r"(sd), "n"(TB));
}
template<int TB> __device__ __forceinline__ void wgmma_rs_n24(float* d, uint32_t a0, uint32_t a1, uint32_t a2, uint32_t a3, uint64_t db, int sd){
  asm volatile("{ .reg .pred p; setp.ne.b32 p, %17, 0; wgmma.mma_async.sync.aligned.m64n24k16.f32.bf16.bf16 {%0,%1,%2,%3,%4,%5,%6,%7,%8,%9,%10,%11}, {%12,%13,%14,%15}, %16, p, 1, 1, %18; }"
   : "+f"(d[0]),"+f"(d[1]),"+f"(d[2]),"+f"(d[3]),"+f"(d[4]),"+f"(d[5]),"+f"(d[6]),"+f"(d[7]),"+f"(d[8]),"+f"(d[9]),"+f"(d[10]),"+f"(d[11]) : "r"(a0),"r"(a1),"r"(a2),"r"(a3), "l"(db), "r"(sd), "n"(TB));
}
template<int TB> __device__ __forceinline__ void wgmma_rs_n32(float* d, uint32_t a0, uint32_t a1, uint32_t a2, uint32_t a3, uint64_t db, int sd){
  asm volatile("{ .reg .pred p; setp.ne.b32 p, %21, 0; wgmma.mma_async.sync.aligned.m64n32k16.f32.bf16.bf16 {%0,%1,%2,%3,%4,%5,%6,%7,%8,%9,%10,%11,%12,%13,%14,%15}, {%16,%17,%18,%19}, %20, p, 1, 1, %22; }"
   : "+f"(d[0]),"+f"(d[1]),"+f"(d[2]),"+f"(d[3]),"+f"(d[4]),"+f"(d[5]),"+f"(d[6]),"+f"(d[7]),"+f"(d[8]),"+f"(d[9]),"+f"(d[10]),"+f"(d[11]),"+f"(d[12]),"+f"(d[13]),"+f"(d[14]),"+f"(d[15]) : "r"(a0),"r"(a1),"r"(a2),"r"(a3), "l"(db), "r"(sd), "n"(TB));
}
template<int TB> __device__ __forceinline__ void wgmma_rs_n40(float* d, uint32_t a0, uint32_t a1, uint32_t a2, uint32_t a3, uint64_t db, int sd){
  asm volatile("{ .reg .pred p; setp.ne.b32 p, %25, 0; wgmma.mma_async.sync.aligned.m64n40k16.f32.bf16.bf16 {%0,%1,%2,%3,%4,%5,%6,%7,%8,%9,%10,%11,%12,%13,%14,%15,%16,%17,%18,%19}, {%20,%21,%22,%23}, %24, p, 1, 1, %26; }"
   : "+f"(d[0]),"+f"(d[1]),"+f"(d[2]),"+f"(d[3]),"+f"(d[4]),"+f"(d[5]),"+f"(d[6]),"+f"(d[7]),"+f"(d[8]),"+f"(d[9]),"+f"(d[10]),"+f"(d[11]),"+f"(d[12]),"+f"(d[13]),"+f"(d[14]),"+f"(d[15]),"+f"(d[16]),"+f"(d[17]),"+f"(d[18]),"+f"(d[19]) : "r"(a0),"r"(a1),"r"(a2),"r"(a3), "l"(db), "r"(sd), "n"(TB));
}
template<int TB> __device__ __forceinline__ void wgmma_rs_n48(float* d, uint32_t a0, uint32_t a1, uint32_t a2, uint32_t a3, uint64_t db, int sd){
  asm volatile("{ .reg .pred p; setp.ne.b32 p, %29, 0; wgmma.mma_async.sync.aligned.m64n48k16.f32.bf16.bf16 {%0,%1,%2,%3,%4,%5,%6,%7,%8,%9,%10,%11,%12,%13,%14,%15,%16,%17,%18,%19,%20,%21,%22,%23}, {%24,%25,%26,%27}, %28, p, 1, 1, %30; }"
   : "+f"(d[0]),"+f"(d[1]),"+f"(d[2]),"+f"(d[3]),"+f"(d[4]),"+f"(d[5]),"+f"(d[6]),"+f"(d[7]),"+f"(d[8]),"+f"(d[9]),"+f"(d[10]),"+f"(d[11]),"+f"(d[12]),"+f"(d[13]),"+f"(d[14]),"+f"(d[15]),"+f"(d[16]),"+f"(d[17]),"+f"(d[18]),"+f"(d[19]),"+f"(d[20]),"+f"(d[21]),"+f"(d[22]),"+f"(d[23]) : "r"(a0),"r"(a1),"r"(a2),"r"(a3), "l"(db), "r"(sd), "n"(TB));
}
template<int TB> __device__ __forceinline__ void wgmma_rs_n56(float* d, uint32_t a0, uint32_t a1, uint32_t a2, uint32_t a3, uint64_t db, int sd){
  asm volatile("{ .reg .pred p; setp.ne.b32 p, %33, 0; wgmma.mma_async.sync.aligned.m64n56k16.f32.bf16.bf16 {%0,%1,%2,%3,%4,%5,%6,%7,%8,%9,%10,%11,%12,%13,%14,%15,%16,%17,%18,%19,%20,%21,%22,%23,%24,%25,%26,%27}, {%28,%29,%30,%31}, %32, p, 1, 1, %34; }"
   : "+f"(d[0]),"+f"(d[1]),"+f"(d[2]),"+f"(d[3]),"+f"(d[4]),"+f"(d[5]),"+f"(d[6]),"+f"(d[7]),"+f"(d[8]),"+f"(d[9]),"+f"(d[10]),"+f"(d[11]),"+f"(d[12]),"+f"(d[13]),"+f"(d[14]),"+f"(d[15]),"+f"(d[16]),"+f"(d[17]),"+f"(d[18]),"+f"(d[19]),"+f"(d[20]),"+f"(d[21]),"+f"(d[22]),"+f"(d[23]),"+f"(d[24]),"+f"(d[25]),"+f"(d[26]),"+f"(d[27]) : "r"(a0),"r"(a1),"r"(a2),"r"(a3), "l"(db), "r"(sd), "n"(TB));
}
template<int TB> __device__ __forceinline__ void wgmma_rs_n64(float* d, uint32_t a0, uint32_t a1, uint32_t a2, uint32_t a3, uint64_t db, int sd){
  asm volatile("{ .reg .pred p; setp.ne.b32 p, %37, 0; wgmma.mma_async.sync.aligned.m64n64k16.f32.bf16.bf16 {%0,%1,%2,%3,%4,%5,%6,%7,%8,%9,%10,%11,%12,%13,%14,%15,%16,%17,%18,%19,%20,%21,%22,%23,%24,%25,%26,%27,%28,%29,%30,%31}, {%32,%33,%34,%35}, %36, p, 1, 1, %38; }"
   : "+f"(d[0]),"+f"(d[1]),"+f"(d[2]),"+f"(d[3]),"+f"(d[4]),"+f"(d[5]),"+f"(d[6]),"+f"(d[7]),"+f"(d[8]),"+f"(d[9]),"+f"(d[10]),"+f"(d[11]),"+f"(d[12]),"+f"(d[13]),"+f"(d[14]),"+f"(d[15]),"+f"(d[16]),"+f"(d[17]),"+f"(d[18]),"+f"(d[19]),"+f"(d[20]),"+f"(d[21]),"+f"(d[22]),"+f"(d[23]),"+f"(d[24]),"+f"(d[25]),"+f"(d[26]),"+f"(d[27]),"+f"(d[28]),"+f"(d[29]),"+f"(d[30]),"+f"(d[31]) : "r"(a0),"r"(a1),"r"(a2),"r"(a3), "l"(db), "r"(sd), "n"(TB));
}
template<int N,int TA,int TB> __device__ __forceinline__ void wgmma_ss(float* d, uint64_t da, uint64_t db, int sd){
  if constexpr(N==176) wgmma_ss_n176<TA,TB>(d,da,db,sd);
}
template<int N,int TB> __device__ __forceinline__ void wgmma_rs(float* d, uint32_t a0,uint32_t a1,uint32_t a2,uint32_t a3, uint64_t db, int sd){
  if constexpr(N==8) wgmma_rs_n8<TB>(d,a0,a1,a2,a3,db,sd);
  if constexpr(N==16) wgmma_rs_n16<TB>(d,a0,a1,a2,a3,db,sd);
  if constexpr(N==24) wgmma_rs_n24<TB>(d,a0,a1,a2,a3,db,sd);
  if constexpr(N==32) wgmma_rs_n32<TB>(d,a0,a1,a2,a3,db,sd);
  if constexpr(N==40) wgmma_rs_n40<TB>(d,a0,a1,a2,a3,db,sd);
  if constexpr(N==48) wgmma_rs_n48<TB>(d,a0,a1,a2,a3,db,sd);
  if constexpr(N==56) wgmma_rs_n56<TB>(d,a0,a1,a2,a3,db,sd);
  if constexpr(N==64) wgmma_rs_n64<TB>(d,a0,a1,a2,a3,db,sd);
}


typedef __nv_bfloat16 bf16;
constexpr int S_ = 2048, D_ = 512, F_ = 1376, FS = 176;

__device__ __forceinline__ uint32_t smem_u32(const void* p){ return (uint32_t)__cvta_generic_to_shared(p); }
__device__ __forceinline__ void mbar_init(uint32_t bar, uint32_t cnt){ asm volatile("mbarrier.init.shared::cta.b64 [%0], %1;"::"r"(bar),"r"(cnt):"memory"); }
__device__ __forceinline__ void mbar_expect_tx(uint32_t bar, uint32_t bytes){ asm volatile("mbarrier.arrive.expect_tx.shared::cta.b64 _, [%0], %1;"::"r"(bar),"r"(bytes):"memory"); }
__device__ __forceinline__ void mbar_arrive(uint32_t bar){ asm volatile("mbarrier.arrive.shared::cta.b64 _, [%0];"::"r"(bar):"memory"); }
__device__ __forceinline__ void mbar_arrive_n(uint32_t bar, uint32_t n){ asm volatile("mbarrier.arrive.shared::cta.b64 _, [%0], %1;"::"r"(bar),"r"(n):"memory"); }
__device__ __forceinline__ void mbar_arrive_cl(uint32_t cbar){ asm volatile("mbarrier.arrive.shared::cluster.b64 _, [%0];"::"r"(cbar):"memory"); }
__device__ __forceinline__ uint32_t mapa(uint32_t a, uint32_t cta){ uint32_t r; asm volatile("mapa.shared::cluster.u32 %0, %1, %2;":"=r"(r):"r"(a),"r"(cta)); return r; }
__device__ __forceinline__ void mbar_wait(uint32_t bar, uint32_t ph){
  asm volatile("{ .reg .pred p; .reg .u32 c; mov.u32 c, 0;\n"
               "WL: mbarrier.try_wait.parity.shared::cta.b64 p, [%0], %1; @p bra WD; add.u32 c,c,1; setp.lt.u32 p, c, 1000000; @p bra WL; trap;\n"
               "WD: }"::"r"(bar),"r"(ph):"memory"); }
__device__ __forceinline__ uint32_t mbar_test(uint32_t bar, uint32_t ph){ uint32_t ok; asm volatile("{ .reg .pred p; mbarrier.test_wait.parity.shared::cta.b64 p, [%1], %2; selp.u32 %0,1,0,p; }":"=r"(ok):"r"(bar),"r"(ph):"memory"); return ok; }
__device__ __forceinline__ void spin_guard(int n){ asm volatile("{ .reg .pred p; setp.gt.s32 p, %0, 2000000; @p trap; }"::"r"(n)); }
__device__ __forceinline__ bool elect_one(){ uint32_t p; asm volatile("{ .reg .pred P; elect.sync _|P, 0xffffffff; selp.u32 %0,1,0,P; }":"=r"(p)); return p; }
__device__ __forceinline__ void tma2d(uint32_t dst, const CUtensorMap* m, int c0, int c1, uint32_t bar){
  asm volatile("cp.async.bulk.tensor.2d.shared::cluster.global.mbarrier::complete_tx::bytes [%0], [%1, {%3, %4}], [%2];"::"r"(dst),"l"(m),"r"(bar),"r"(c0),"r"(c1):"memory"); }
__device__ __forceinline__ void tma2d_mc(uint32_t dst, const CUtensorMap* m, int c0, int c1, uint32_t bar){
  asm volatile("cp.async.bulk.tensor.2d.shared::cluster.global.mbarrier::complete_tx::bytes.multicast::cluster [%0], [%1, {%3, %4}], [%2], %5;"::"r"(dst),"l"(m),"r"(bar),"r"(c0),"r"(c1),"h"((uint16_t)3):"memory"); }
__device__ __forceinline__ void wg_fence(){ asm volatile("wgmma.fence.sync.aligned;":::"memory"); }
__device__ __forceinline__ void wg_commit(){ asm volatile("wgmma.commit_group.sync.aligned;":::"memory"); }
template<int N> __device__ __forceinline__ void wg_wait(){ asm volatile("wgmma.wait_group.sync.aligned %0;"::"n"(N):"memory"); }
__device__ __forceinline__ uint64_t make_desc(uint32_t addr, uint32_t lbo, uint32_t sbo, uint32_t sw){ return (uint64_t)((addr&0x3FFFF)>>4) | ((uint64_t)((lbo&0x3FFFF)>>4)<<16) | ((uint64_t)((sbo&0x3FFFF)>>4)<<32) | ((uint64_t)sw<<62); }
__device__ __forceinline__ void ldsm4t(uint32_t a, uint32_t& r0, uint32_t& r1, uint32_t& r2, uint32_t& r3){ asm volatile("ldmatrix.sync.aligned.m8n8.x4.trans.shared.b16 {%0,%1,%2,%3}, [%4];":"=r"(r0),"=r"(r1),"=r"(r2),"=r"(r3):"r"(a):"memory"); }
__device__ __forceinline__ uint32_t pack_bf16(float lo, float hi){ uint32_t r; asm("cvt.rn.bf16x2.f32 %0, %1, %2;":"=r"(r):"f"(hi),"f"(lo)); return r; }
__device__ __forceinline__ float bf_lo(uint32_t v){ return __uint_as_float(v<<16); }
__device__ __forceinline__ float bf_hi(uint32_t v){ return __uint_as_float(v&0xffff0000u); }
__device__ __forceinline__ float rbf(float x){ return __bfloat162float(__float2bfloat16(x)); }
__device__ __forceinline__ uint32_t hadd2_bf16(uint32_t a, uint32_t b){ uint32_t r; asm("add.rn.bf16x2 %0, %1, %2;":"=r"(r):"r"(a),"r"(b)); return r; }
__device__ __forceinline__ float tanh_fast(float x){ float r; asm("tanh.approx.f32 %0, %1;":"=f"(r):"f"(x)); return r; }

__device__ __forceinline__ void st_rlx128(void* p, uint32_t a, uint32_t b, uint32_t c, uint32_t d){
  asm volatile("{ .reg .b64 l,h; .reg .b128 v; mov.b64 l,{%1,%2}; mov.b64 h,{%3,%4}; mov.b128 v,{l,h}; st.relaxed.gpu.global.b128 [%0], v; }"::"l"(p),"r"(a),"r"(b),"r"(c),"r"(d):"memory"); }
__device__ __forceinline__ void ld_rlx128(const void* p, uint4& v){
  asm volatile("{ .reg .b64 l,h; .reg .b128 v; ld.relaxed.gpu.global.b128 v, [%4]; mov.b128 {l,h}, v; mov.b64 {%0,%1}, l; mov.b64 {%2,%3}, h; }":"=r"(v.x),"=r"(v.y),"=r"(v.z),"=r"(v.w):"l"(p):"memory"); }
__device__ __forceinline__ void st_async128(uint32_t dst, uint32_t a, uint32_t b, uint32_t c, uint32_t d, uint32_t cbar){
  asm volatile("st.async.weak.shared::cluster.mbarrier::complete_tx::bytes.v4.b32 [%0], {%1,%2,%3,%4}, [%5];"::"r"(dst),"r"(a),"r"(b),"r"(c),"r"(d),"r"(cbar)); }
__device__ __forceinline__ void bulk_g2s(uint32_t dst, const void* src, uint32_t bytes, uint32_t bar){
  asm volatile("cp.async.bulk.shared::cluster.global.mbarrier::complete_tx::bytes [%0], [%1], %2, [%3];"::"r"(dst),"l"(src),"r"(bytes),"r"(bar):"memory"); }
__device__ __forceinline__ void lds128(uint32_t a, uint32_t& x, uint32_t& y, uint32_t& z, uint32_t& w){ asm volatile("ld.shared.v4.u32 {%0,%1,%2,%3}, [%4];":"=r"(x),"=r"(y),"=r"(z),"=r"(w):"r"(a):"memory"); }
__device__ __forceinline__ void tma4d_red_add(const CUtensorMap* m, int c0, int c1, int c2, int c3, uint32_t src){
  asm volatile("cp.reduce.async.bulk.tensor.4d.global.shared::cta.add.tile.bulk_group [%0, {%1, %2, %3, %4}], [%5];"::"l"(m),"r"(c0),"r"(c1),"r"(c2),"r"(c3),"r"(src):"memory"); }
__device__ __forceinline__ void stsm4_nm(uint32_t a, uint32_t r0, uint32_t r1, uint32_t r2, uint32_t r3){ asm volatile("stmatrix.sync.aligned.m8n8.x4.shared.b16 [%0], {%1,%2,%3,%4};"::"r"(a),"r"(r0),"r"(r1),"r"(r2),"r"(r3)); }
__device__ __forceinline__ void tma3d(uint32_t dst, const CUtensorMap* m, int c0, int c1, int c2, uint32_t bar){
  asm volatile("cp.async.bulk.tensor.3d.shared::cluster.global.mbarrier::complete_tx::bytes [%0], [%1, {%3, %4, %5}], [%2];"::"r"(dst),"l"(m),"r"(bar),"r"(c0),"r"(c1),"r"(c2):"memory"); }
__device__ __forceinline__ uint32_t lds32(uint32_t a){ uint32_t v; asm volatile("ld.shared.u32 %0, [%1];":"=r"(v):"r"(a)); return v; }
__device__ __forceinline__ void sts128(uint32_t a, uint32_t x, uint32_t y, uint32_t z, uint32_t w){ asm volatile("st.shared.v4.u32 [%0], {%1,%2,%3,%4};"::"r"(a),"r"(x),"r"(y),"r"(z),"r"(w):"memory"); }
__device__ __forceinline__ uint4 ldg_nc128(const void* p){ uint4 v; asm volatile("ld.global.nc.L1::no_allocate.v4.u32 {%0,%1,%2,%3}, [%4];":"=r"(v.x),"=r"(v.y),"=r"(v.z),"=r"(v.w):"l"(p)); return v; }
__device__ __forceinline__ uint32_t hmul2_bf16(uint32_t a, uint32_t b){ uint32_t r; asm("mul.rn.bf16x2 %0, %1, %2;":"=r"(r):"r"(a),"r"(b)); return r; }
__device__ __forceinline__ uint32_t hfma2_bf16(uint32_t a, uint32_t b, uint32_t c){ uint32_t r; asm("fma.rn.bf16x2 %0, %1, %2, %3;":"=r"(r):"r"(a),"r"(b),"r"(c)); return r; }
__device__ __forceinline__ uint32_t hsub2_bf16(uint32_t a, uint32_t b){ uint32_t r; asm("sub.rn.bf16x2 %0, %1, %2;":"=r"(r):"r"(a),"r"(b)); return r; }
__device__ __forceinline__ void signal_add(unsigned* p){ asm volatile("fence.acq_rel.gpu;":::"memory"); asm volatile("red.relaxed.gpu.global.add.u32 [%0], 1;"::"l"(p):"memory"); }
__device__ __forceinline__ void lds128_nm(uint32_t a, uint32_t& x, uint32_t& y, uint32_t& z, uint32_t& w){ asm volatile("ld.shared.v4.u32 {%0,%1,%2,%3}, [%4];":"=r"(x),"=r"(y),"=r"(z),"=r"(w):"r"(a)); }
__device__ __forceinline__ float ln_rstd(float var){
  float sq, r; asm("sqrt.approx.f32 %0, %1;":"=f"(sq):"f"(rbf(rbf(var)+1e-5f))); asm("rcp.approx.f32 %0, %1;":"=f"(r):"f"(rbf(sq))); return r; }
__device__ __forceinline__ float4 gather_sum(const uint4* src, int n, int stride, uint32_t par){
  float4 c=make_float4(0.f,0.f,0.f,0.f);
  #pragma unroll 1
  for(int kb=0;kb<n;kb+=4){
    uint4 v[4]; int it=0;
    do{
      #pragma unroll
      for(int u=0;u<4;u++) ld_rlx128(src+u*stride, v[u]);
      spin_guard(++it);
    }while(((v[0].x^par)|(v[1].x^par)|(v[2].x^par)|(v[3].x^par))&1);
    #pragma unroll
    for(int u=0;u<4;u++){ c.x+=__uint_as_float(v[u].x); c.y+=__uint_as_float(v[u].y); c.z+=__uint_as_float(v[u].z); c.w+=__uint_as_float(v[u].w); }
    src+=4*stride;
  }
  return c;
}
__host__ __device__ __forceinline__ int pos2row(int pos){
  const int P = 1 - (pos >> 10), thr = (pos & 1023) >> 3, k = (pos>>2)&1, h = (pos>>1)&1, e = pos&1;
  const int w = thr >> 5, tp = (thr >> 3)&3, j = (thr >> 1)&3, p = thr & 1;
  return 16*(127 - (64*P + 16*j + 8*k + 2*tp + e)) + 8*h + 2*w + p;
}

__device__ __align__(1024) bf16 g_hT[D_*S_];
__device__ __align__(1024) uint4 g_xa[128*128*8];
__device__ __align__(1024) uint4 g_qs[128*8];
__device__ uint4 g_stat[16*2*8*32];
__device__ uint4 g_csp[8*16*88];
__device__ uint4 g_cs2[8*96];
__device__ unsigned g_cnt[4*32];

constexpr int QDELAY = 2000, KV0 = 3, XAFTER = 5, XPOS = 3, ZKV = 3, WSTART = 6, W9 = 2, PACE = 3, CSLEEP = 600, SKW = 2, STX0 = 2, STX1 = 2, CSUN = 4, HF = 3, NIN = 7;
constexpr int CSU = CSUN;
constexpr uint32_t G2_CH = 0x33221010u, G2_PEER = 0xAC;
constexpr int NS = 6, WSLOT = 24576, NX = 4, XSLOT = 8192;
constexpr int OFF_RES0 = 0, OFF_X = 8192, OFF_RES1 = 73728, OFF_W = 81920;
constexpr int OFF_CS = OFF_W + NS*WSLOT, OFF_ROW = OFF_CS + 2*FS*4, OFF_BAR = OFF_ROW + 1024;
constexpr int TBL = 8320, UPL = 2112, UCH = 2*UPL, QP = 1088, KVCH = 4224;
constexpr int OFF_TBL = 32768, OFF_U = OFF_TBL + 4*TBL, OFF_XAL = 82944, OFF_XAE = OFF_W + 2*WSLOT;
constexpr int OFF_IMG = 0, OFF_X8 = OFF_XAL + 16384, OFF_ZB = OFF_W + WSLOT - 2048, EXB = 32*144;
#define KVOFF(T) (OFF_W + 3*WSLOT + (T)*KVCH - ((T)>>2)*(2*WSLOT+4*KVCH))
constexpr int OFF_KV = OFF_W + 3*WSLOT, OFF_Q = OFF_W + 4*WSLOT;
static_assert(OFF_X8 + EXB <= OFF_ZB && OFF_U + 4*UCH <= OFF_XAL && OFF_XAL + 16384 <= OFF_W + WSLOT, "overlay");
constexpr int B_WFULL = 0, B_WEMPTY = B_WFULL+NS, B_XFULL = B_WEMPTY+NS, B_XEMPTY = B_XFULL+2*NX, B_PRDY = B_XEMPTY+2*NX, B_AFULL = B_PRDY+2,
              B_ONE = B_AFULL+2, B_FB = B_ONE, B_INIT = B_FB+2, B_XA = B_INIT+2, B_PAR = B_XA+2, B_TD = B_PAR+2, B_KV = B_TD+1, B_U = B_KV+8, B_HD = B_U+8, B_Q = B_HD+2, B_QD = B_Q+8, B_SC = B_QD+1, B_X03 = B_SC+1, B_RT = B_X03+1, NBAR = B_RT+2;
constexpr int OFF_MISC = (OFF_BAR + NBAR*8 + 15)&~15;
constexpr int OFF_TGT = OFF_MISC + 16;
constexpr int SMEM_BYTES = OFF_TGT + 16;
static_assert(SMEM_BYTES<=232448,"smem");

struct Maps { CUtensorMap k, v, xa, w64, w48, wd, ht, out, out8; int upfirst; };

__device__ __forceinline__ void load_w_stage(const Maps& maps, uint32_t dst, int col, int k0, uint32_t fb){
  asm volatile("cp.async.bulk.tensor.4d.shared::cluster.global.mbarrier::complete_tx::bytes [%0], [%1, {%3, %4, %5, %5}], [%2];"::"r"(dst),"l"(&maps.w64),"r"(fb),"r"(col),"r"(k0),"r"(0):"memory");
  tma3d(dst+16384, &maps.w48, col+128, k0, 0, fb);
}

template<int N> __device__ __forceinline__ void conv_mma(float* acc, const uint32_t* R, uint64_t db){
  wgmma_rs<N,0>(acc, R[0],R[1],R[2],R[3], db,   1);
  wgmma_rs<N,0>(acc, R[4],R[5],R[6],R[7], db+1, 1);
}
__device__ __forceinline__ void conv_lda(uint32_t* R, const uint32_t* tb, int off){
  R[0]=lds32(tb[0]+off); R[1]=lds32(tb[1]+off); R[3]=lds32(tb[2]+off); R[5]=lds32(tb[3]+off); R[7]=lds32(tb[4]+off);
}
__device__ __forceinline__ void conv_dup(uint32_t* R){
  asm volatile("mov.b32 %0, %1;":"=r"(R[2]):"r"(R[1])); asm volatile("mov.b32 %0, %1;":"=r"(R[4]):"r"(R[3])); asm volatile("mov.b32 %0, %1;":"=r"(R[6]):"r"(R[5]));
}
__device__ __forceinline__ void zero4(float* a){
  #pragma unroll
  for(int i=0;i<4;i+=2) asm volatile("mov.b64 {%0,%1}, 0;":"=f"(a[i]),"=f"(a[i+1]));
}
__device__ __forceinline__ uint32_t tid_now(){ uint32_t t; asm volatile("mov.u32 %0, %%tid.x;":"=r"(t)); return t; }
__device__ __forceinline__ void load_xs(uint4* x, uint4* st, uint32_t sb, int warp, int lane){
  const uint32_t tw = (warp&3)*32+lane, pc = ((warp>>2)*2)^(tw&7);
  #pragma unroll
  for(int i=0;i<4;i++) lds128(sb+OFF_XAL+tw*128+((pc^(i&1)^((i>>1)*4))<<4), x[i].x,x[i].y,x[i].z,x[i].w);
  #pragma unroll
  for(int i=0;i<8;i++) lds128(sb+OFF_XAE+tw*128+((i^(tw&7))<<4), st[i].x,st[i].y,st[i].z,st[i].w);
}
__device__ __forceinline__ void check_xs(uint4* x, uint4* st, uint32_t ep, uint32_t sb, int warp){
  for(int n=0;n<2000000;n++){
    uint32_t bad=0;
    #pragma unroll
    for(int i=0;i<8;i++) bad|=st[i].w^ep;
    if(!bad && x[0].x && x[1].x && x[2].x && x[3].x) break;
    const uint32_t t2=tid_now()&127, pc = ((warp>>2)*2)^(t2&7);
    #pragma unroll
    for(int i=0;i<4;i++) ld_rlx128(&g_xa[blockIdx.x*1024+t2*8+(pc^(i&1)^((i>>1)*4))], x[i]);
    #pragma unroll
    for(int i=0;i<8;i++) ld_rlx128(&g_qs[t2*8+(i^(t2&7))], st[i]);
  }
  __syncwarp();
}
__device__ __forceinline__ void ln_x(uint4* x, const uint4* st, uint4* a){
#define LNA(X,S) ({ const uint32_t d_=hsub2_bf16(X,S.x); hfma2_bf16(d_,S.y,hmul2_bf16(d_,S.z)); })
  #pragma unroll
  for(int i=0;i<2;i++){
    x[i].x=~x[i].x;
    a[i].x=LNA(x[i].x,st[0]); a[i].y=LNA(x[i].y,st[1]); a[i].z=LNA(x[i].z,st[2]); a[i].w=LNA(x[i].w,st[3]);
  }
}
template<int PART> __device__ __forceinline__ uint32_t ex_buf(uint32_t sb, int warp){
  return sb + (PART? (warp<7? OFF_IMG+warp*EXB : OFF_X8) : ((warp&3)<3? OFF_TBL+(warp>>2)*2*TBL+(warp&3)*EXB : OFF_XAL+(warp>>2)*EXB)); }
template<int PART> __device__ __forceinline__ void conv_put(const float* a0, const float* a1, uint4& e0, uint32_t sb, int warp, int lane){
  const uint32_t ad = ex_buf<PART>(sb,warp) + ((lane&24)|((lane&3)<<1)|((lane>>2)&1))*144;
  if(PART) sts128(ad+128, 0,0,0,0); else sts128(ad+128, e0.x,e0.y,e0.z,e0.w);
  #pragma unroll
  for(int ii=0;ii<8;ii++){
    const uint32_t w0=pack_bf16(a0[4*ii],a0[4*ii+1]), w1=pack_bf16(a0[4*ii+2],a0[4*ii+3]), w2=pack_bf16(a1[4*ii],a1[4*ii+1]), w3=pack_bf16(a1[4*ii+2],a1[4*ii+3]);
    sts128(ad+ii*16, w0,w1,w2,w3);
    if(PART && ii==0) e0=make_uint4(w0,w1,w2,w3);
  }
  __syncwarp();
}
template<int PART> __device__ __forceinline__ void conv_get(const uint4* x, const uint4* a, uint32_t sb, int warp, int lane){
  const int cb = blockIdx.x, chl = (warp>>2)*2;
  const uint32_t tw = (warp&3)*32+lane;
  const uint32_t eb = ex_buf<PART>(sb,warp) + (lane&1)*144 + (lane&6)*16 + (lane>>3)*288;
  uint4 d[4][2];
  #pragma unroll
  for(int c=0;c<4;c++){
    const uint32_t ad = eb + c*(8*144+288) - (((lane>>3)+c>3)? 4*288-16 : 0);
    lds128(ad, d[c][0].x,d[c][0].y,d[c][0].z,d[c][0].w);
    lds128(ad+16, d[c][1].x,d[c][1].y,d[c][1].z,d[c][1].w);
  }
#define SUM4(K,F) hadd2_bf16(hadd2_bf16(d[0][K].F,d[1][K].F),hadd2_bf16(d[2][K].F,d[3][K].F))
  uint4 o0, o1;
  o0.x=hadd2_bf16(x[0].x,hmul2_bf16(a[0].x,SUM4(0,x))); o0.y=hadd2_bf16(x[0].y,hmul2_bf16(a[0].y,SUM4(0,y)));
  o0.z=hadd2_bf16(x[0].z,hmul2_bf16(a[0].z,SUM4(1,x))); o0.w=hadd2_bf16(x[0].w,hmul2_bf16(a[0].w,SUM4(1,y)));
  o1.x=hadd2_bf16(x[1].x,hmul2_bf16(a[1].x,SUM4(0,z))); o1.y=hadd2_bf16(x[1].y,hmul2_bf16(a[1].y,SUM4(0,w)));
  o1.z=hadd2_bf16(x[1].z,hmul2_bf16(a[1].z,SUM4(1,z))); o1.w=hadd2_bf16(x[1].w,hmul2_bf16(a[1].w,SUM4(1,w)));
  uint4* dst = (uint4*)(g_hT + (cb*4+chl)*2048 + (1-PART)*1024) + tw;
  const uint32_t par = lds32(sb+OFF_MISC)&1;
  o0.x=(o0.x&~1u)|par; o1.x=(o1.x&~1u)|par;
  dst[0]=o0; dst[256]=o1;
}

__device__ __forceinline__ bool x_bad(uint32_t sb, int wg, int wq, int lane){
  const uint32_t xbase = sb+OFF_X+wg*NX*XSLOT, rbase = sb+(wg? OFF_RES1:OFF_RES0), par = lds32(sb+OFF_MISC), co = lane*128+(((2*wq)^(lane&7))<<4);
  uint32_t bad=0;
  #pragma unroll
  for(int i=0;i<8;i++) bad |= lds32((i<6? xbase+i*4096 : rbase+(i-6)*4096)+co)^par;
  return __any_sync(~0u, bad&1);
}
__device__ __forceinline__ void first_x(const Maps& maps, uint32_t sb, int w){
  const int b = blockIdx.x, rank = b&1, rt = b>>3;
  const uint32_t bar = sb+OFF_BAR, xf = bar+8*(B_XFULL+w*NX), xd = sb+OFF_X+w*NX*XSLOT+rank*4096, rb = sb+(w? OFF_RES1:OFF_RES0);
  const int c0 = w*1024+rt*64, k0 = (rt>>1)+w*(SKW/2), cr = rank*256+((b>>1)&3)*64;
  mbar_expect_tx(xf, 4*XSLOT); mbar_arrive(xf+8); mbar_arrive(xf+16);
  const unsigned tgt = lds32(sb+OFF_TGT+(w? 0:12));
  mbar_wait(bar+8*(B_HD+w), 0);
  {
    unsigned v; int n=0;
    asm volatile("red.relaxed.gpu.global.add.u32 [%0], 1;"::"l"(&g_cnt[w? 0:96]):"memory");
    do{ asm volatile("ld.relaxed.gpu.global.u32 %0, [%1];":"=r"(v):"l"(&g_cnt[w? 0:96]):"memory"); }while((int)(v-tgt)<0 && ++n<2000000);
  }
  tma2d_mc(xd,         &maps.ht, c0, (k0&7)*64+rank*32,     xf);
  tma2d_mc(xd+XSLOT,   &maps.ht, c0, ((k0+1)&7)*64+rank*32, xf);
  tma2d_mc(xd+2*XSLOT, &maps.ht, c0, ((k0+2)&7)*64+rank*32, xf);
  tma2d(rb,      &maps.ht, c0, cr,    xf);
  tma2d(rb+4096, &maps.ht, c0, cr+32, xf);
}

__global__ void __cluster_dims__(2,1,1) __launch_bounds__(384,1)
fused_kernel(const __grid_constant__ Maps maps, const bf16* __restrict__ q, const bf16* __restrict__ shk, const bf16* __restrict__ ssmk,
             const bf16* __restrict__ ssmD, const bf16* __restrict__ wdn, bf16* __restrict__ out){
  extern __shared__ __align__(1024) uint8_t smem_raw[];
  if(threadIdx.x<32){ if(elect_one()){ asm volatile("cp.async.bulk.prefetch.L2.global [%0], 16384;"::"l"(q+blockIdx.x*8192)); } }
  unsigned c_begin; asm volatile("mov.u32 %0, %%clock;":"=r"(c_begin));
  const uint32_t sb = smem_u32(smem_raw);
  const int tid = threadIdx.x, lane = tid&31;
  const int warp = __shfl_sync(0xffffffffu, tid>>5, 0);
  const int wg = warp>>2;
  const int b = blockIdx.x, rank = b&1;
  const int f = b&7, rt = b>>3, fp = f>>1;
  const uint32_t bar = sb+OFF_BAR;

  if(wg==2){
    asm volatile("setmaxnreg.dec.sync.aligned.u32 56;");
    const int cg = b>>1;
    const int cb = cg*2+rank;
    unsigned epoch = 0; uint4 shw = make_uint4(0,0,0,0); uint2 dd = make_uint2(0,0);
    if(warp==11) asm volatile("ld.relaxed.gpu.global.u32 %0, [%1];":"=r"(epoch):"l"(&g_cnt[(lane&3)*32]));
    if(warp!=9){
      shw = ldg_nc128(shk + (cg*8+(lane&3)*2)*4);
      asm volatile("ld.global.nc.v2.u32 {%0,%1}, [%2];":"=r"(dd.x),"=r"(dd.y):"l"(ssmD + cb*4));
    }
    auto ldkv=[&](int i){
      const uint32_t fb=bar+8*(B_KV+i);
      mbar_expect_tx(fb, 2176+2048);
      tma3d(sb+KVOFF(i),      &maps.k, cg*8, i*32+rank*16-1, 0, fb);
      tma3d(sb+KVOFF(i)+2176, &maps.v, cg*8, i*32+rank*16,   0, fb);
    };
    if(warp==9){
      if(lane<3) asm volatile("prefetch.tensormap [%0];"::"l"(&maps.k+lane):"memory");
    }
    asm volatile("bar.sync 0;":::"memory");
    asm volatile("barrier.cluster.arrive.relaxed.aligned;":::"memory");
    if(warp==9){
      { unsigned c1; do{ asm volatile("mov.u32 %0, %%clock;":"=r"(c1)); }while(c1-c_begin<QDELAY); }
      if(elect_one()){
        #pragma unroll
        for(int i=0;i<KV0;i++) ldkv(i);
      }
      __syncwarp();
      mbar_wait(bar+8*B_QD, 0);
      if(elect_one()){
        asm volatile("cp.async.bulk.tensor.2d.global.shared::cta.bulk_group [%0, {%1, %2}], [%3];"::"l"(&maps.xa),"r"(b*64),"r"(0),"r"(sb+OFF_IMG):"memory");
        asm volatile("cp.async.bulk.commit_group;":::"memory");
        #pragma unroll 1
        for(int i=KV0;i<8;i++){
          ldkv(i);
          if(i==XAFTER){
            asm volatile("cp.async.bulk.wait_group.read 0;":::"memory");
            mbar_wait(bar+8*(B_KV+XPOS), 0);
            mbar_expect_tx(bar+8*B_XA, 32768); bulk_g2s(sb+OFF_XAL, &g_xa[cb*1024], 16384, bar+8*B_XA); bulk_g2s(sb+OFF_XAE, g_qs, 16384, bar+8*B_XA);
          }
        }
        mbar_wait(bar+8*B_WEMPTY, 0);
        mbar_wait(bar+8*(B_KV+ZKV), 0);
        #pragma unroll
        for(int i=0;i<8;i++) asm volatile("cp.async.bulk.global.shared::cta.bulk_group [%0], [%1], 2048;"::"l"(out+b*8192+i*1024),"r"(sb+OFF_ZB):"memory");
        asm volatile("cp.async.bulk.commit_group;":::"memory");
        mbar_wait(bar+8*(B_KV+WSTART), 0);
        #pragma unroll 1
        for(int it=0;it<W9;it++){
          mbar_wait(bar+8*(B_WEMPTY+it), 0);
          if(it>=PACE) mbar_wait(bar+8*(B_WFULL+it-PACE), 0);
          mbar_expect_tx(bar+8*(B_WFULL+it), 22528);
          load_w_stage(maps, sb+OFF_W+(5-it)*WSLOT, f*FS, ((it+(rt&14))&15)*32, bar+8*(B_WFULL+it));
        }
        asm volatile("cp.async.bulk.wait_group 0;":::"memory");
        asm volatile("fence.proxy.async.global;":::"memory");
        mbar_arrive(bar+8*(B_HD+1));
      }
      __syncwarp();
    }
    if(warp==11){
      asm volatile("":"+r"(epoch));
      epoch = (epoch>>7)+1;
      if(lane<4) asm volatile("st.shared.u32 [%0], %1;"::"r"(sb+OFF_TGT+lane*4),"r"(epoch<<7):"memory");
      if(lane==0) sts128(sb+OFF_MISC, epoch, dd.x, dd.y, 0);
      __syncwarp();
      if(lane==0) mbar_arrive(bar+8*B_SC);
    }
    if(warp==8 && lane<6) asm volatile("prefetch.tensormap [%0];"::"l"(&maps.w64+lane):"memory");
    mbar_wait(bar+8*B_SC, 0);
    epoch = lds32(sb+OFF_MISC);
    const uint32_t par = epoch&1;
    auto ldx=[&](int w, int it){
      const uint32_t fb = bar+8*(B_XFULL+w*NX+(it&3));
      mbar_expect_tx(fb, XSLOT);
      tma2d_mc(sb+OFF_X+(w*NX+(it&3))*XSLOT+rank*4096, &maps.ht, w*1024+rt*64, ((it+(rt>>1)+w*(SKW/2))&7)*64+rank*32, fb);
    };
    if(warp!=9){
      const int cp = lane&3;
      uint32_t sw[4];
      { const uint4 w = shw;
        sw[0]=__byte_perm(w.x,w.z,0x5410); sw[1]=__byte_perm(w.x,w.z,0x7632); sw[2]=__byte_perm(w.y,w.w,0x5410); sw[3]=__byte_perm(w.y,w.w,0x7632); }
      const uint32_t udst = mapa(sb+OFF_U+(cp&1)*2*UCH, cp>>1), ubar = mapa(bar+8*B_U, cp>>1);
      asm volatile("barrier.cluster.wait.aligned;":::"memory");
      #pragma unroll 1
      for(int tk=(warp==8? 2:warp-10); tk<16; tk+=3){
        const int T=tk>>1, gl=(tk&1)*8+(lane>>2);
        mbar_wait(bar+8*(B_KV+T), 0);
        const uint32_t ka = sb+KVOFF(T)+gl*16+cp*4, va = ka+2176;
        uint32_t kk[11], u[8];
        #pragma unroll
        for(int r=0;r<3;r++) kk[r]=lds32(ka+(5+r)*272);
        #pragma unroll
        for(int r=0;r<8;r++){ kk[3+r]=lds32(ka+16+r*272); u[r]=lds32(va+r*256); }
        #pragma unroll
        for(int r=0;r<8;r++){
          uint32_t a=hmul2_bf16(kk[r],sw[3]); a=hadd2_bf16(a,hmul2_bf16(kk[r+1],sw[2])); a=hadd2_bf16(a,hmul2_bf16(kk[r+2],sw[1])); a=hadd2_bf16(a,hmul2_bf16(kk[r+3],sw[0]));
          u[r]=hmul2_bf16(a,u[r]);
        }
        const int R = 255-(T*32+rank*16+gl);
        const uint32_t d = udst + (R&1)*UPL + (R>>1)*16;
        st_async128(d,     __byte_perm(u[7],u[6],0x5410), __byte_perm(u[5],u[4],0x5410), __byte_perm(u[3],u[2],0x5410), __byte_perm(u[1],u[0],0x5410), ubar+8*T);
        st_async128(d+UCH, __byte_perm(u[7],u[6],0x7632), __byte_perm(u[5],u[4],0x7632), __byte_perm(u[3],u[2],0x7632), __byte_perm(u[1],u[0],0x7632), ubar+8*T);
      }
      __syncwarp();
      if(lane==0) mbar_arrive(bar+8*B_TD);
    } else {
      asm volatile("barrier.cluster.wait.aligned;":::"memory");
    }
    if(warp==8){
      if(elect_one()){
        const int col = f*FS;
        #pragma unroll
        for(int it=W9; it<NS; it++){
          mbar_wait(bar+8*(B_WEMPTY+it), 0);
          if(it==4) mbar_wait(bar+8*B_TD, 0);
          if(it==5) mbar_wait(bar+8*(B_HD+1), 0);
          if(it>=PACE) mbar_wait(bar+8*(B_WFULL+it-PACE), 0);
          mbar_expect_tx(bar+8*(B_WFULL+it), 22528);
          load_w_stage(maps, sb+OFF_W+(5-it)*WSLOT, col, ((it+(rt&14))&15)*32, bar+8*(B_WFULL+it));
        }
        mbar_wait(bar+8*(B_INIT+1), 0);
        mbar_wait(bar+8*B_X03, 0); ldx(0,3);
        uint32_t wb = bar, dst = sb+OFF_W+5*WSLOT, ph = 1; int k0 = ((6+(rt&14))&15)*32;
        #pragma unroll 1
        for(int j=4; j<4+(10+SKW)/2; j++){
          mbar_wait(wb+8*B_WEMPTY, ph);
          mbar_expect_tx(wb, 22528);       load_w_stage(maps, dst, col, k0, wb);
          mbar_wait(wb+8*B_WEMPTY+8, ph);
          mbar_expect_tx(wb+8, 22528);     load_w_stage(maps, dst-WSLOT, col, k0+32, wb+8);
          if(j<8){ mbar_wait(bar+8*(B_XEMPTY+(j&3)), 0); ldx(0,j); }
          const int j1 = j-SKW/2;
          if(j1>=4 && j1<8){ if(j1==4) mbar_wait(bar+8*(B_FB+1), 0); mbar_wait(bar+8*(B_XEMPTY+NX+(j1&3)), 0); ldx(1,j1); }
          if(j==5) asm volatile("cp.async.bulk.prefetch.L2.global [%0], 11008;"::"l"(wdn+b*5504):"memory");
          const bool wrap = wb==bar+32;
          wb = wrap? bar : wb+16; dst = wrap? dst+4*WSLOT : dst-2*WSLOT; ph ^= wrap; k0 = (k0+64)&511;
        }
        #pragma unroll
        for(int j=0;j<8;j++){
          constexpr int I0=16+SKW;
          const int slot=(I0+j)%NS, ci=(G2_CH>>(4*j))&3, kh=((G2_PEER>>j)&1)^rank;
          mbar_wait(bar+8*(B_WEMPTY+slot), ((I0+j)/NS)&1);
          mbar_expect_tx(bar+8*(B_WFULL+slot), 22528);
          tma2d(sb+OFF_W+(5-slot)*WSLOT, &maps.wd, rank*256+((fp+ci)&3)*64, (2*fp+kh)*FS, bar+8*(B_WFULL+slot));
        }
      }
      __syncwarp();
    } else if(warp==11){
      if(elect_one()){
        #pragma unroll 1
        for(int w=0;w<2;w++){ first_x(maps, sb, w); }
        mbar_arrive(bar+8*(B_INIT+1));
      }
      __syncwarp();
      __nanosleep(CSLEEP);
      {
        const int j = rt*6+(lane>>2);
        float4 c = make_float4(0.f,0.f,0.f,0.f);
        if(lane<24 && j<88) c = gather_sum(&g_csp[(f*16+(lane&3)*4)*88+j], 4, 88, par);
        __syncwarp();
        #pragma unroll
        for(int o=1;o<4;o<<=1){ c.x+=__shfl_xor_sync(~0u,c.x,o); c.y+=__shfl_xor_sync(~0u,c.y,o); c.z+=__shfl_xor_sync(~0u,c.z,o); c.w+=__shfl_xor_sync(~0u,c.w,o); }
        if(lane<24 && j<88 && !(lane&3)) st_rlx128(&g_cs2[f*96+j], (__float_as_uint(c.x)&~1u)|par, __float_as_uint(c.y), __float_as_uint(c.z), __float_as_uint(c.w));
      }
      { uint4 v[3]; int n=0; const int j2 = lane<24? lane+64 : lane;
        do{ __nanosleep(CSLEEP); ld_rlx128(&g_cs2[f*96+lane], v[0]); ld_rlx128(&g_cs2[f*96+lane+32], v[1]); ld_rlx128(&g_cs2[f*96+j2], v[2]); spin_guard(++n); }while(((v[0].x^par)|(v[1].x^par)|(v[2].x^par))&1);
        *(uint4*)(smem_raw+OFF_CS+lane*16)=v[0]; *(uint4*)(smem_raw+OFF_CS+(lane+32)*16)=v[1]; *(uint4*)(smem_raw+OFF_CS+j2*16)=v[2]; }
      mbar_wait(bar+8*(B_FB+1), 0);
      __syncwarp();
      if(lane<2) mbar_arrive(bar+8*(B_PAR+lane));
      #pragma unroll 4
      for(int i=0;i<32;i++) g_xa[cb*1024+i*32+lane]=make_uint4(0,0,0,0);
    } else {
      const int w = warp-9;
      mbar_wait(bar+8*(B_HD+w), 0);
      if(elect_one()){
        const unsigned tgt = lds32(sb+OFF_TGT+4+4*w);
        signal_add(&g_cnt[32+32*w]);
        unsigned v; int n=0; do{ asm volatile("ld.acquire.gpu.global.u32 %0, [%1];":"=r"(v):"l"(&g_cnt[32+32*w]):"memory"); spin_guard(++n); }while((int)(v-tgt)<0);
        asm volatile("fence.proxy.async.global;":::"memory");
        if(w) ldx(1,3); else mbar_arrive(bar+8*B_X03);
        mbar_arrive(bar+8*(B_FB+w));
      }
      __syncwarp();
      mbar_wait(bar+8*(B_RT+w), 0);
      {
        __nanosleep(CSLEEP);
        const float4 st=gather_sum(&g_stat[((rt*2+w)*8)*32+lane], 8, 32, par);
        const float s0=st.x, q0=st.y, s1=st.z, q1=st.w;
        const float m0=s0*(1.f/512), m1=s1*(1.f/512);
        const float v0=fmaxf(q0*(1.f/512)-m0*m0,0.f), v1=fmaxf(q1*(1.f/512)-m1*m1,0.f);
        const float r0=ln_rstd(v0), r1=ln_rstd(v1);
        *(float4*)(smem_raw+OFF_ROW+w*512+lane*16)=make_float4(-rbf(m0),r0,-rbf(m1),r1);
        mbar_wait(bar+8*(B_XEMPTY+w*NX+3), 0);
        __syncwarp();
        if(lane==0) mbar_arrive(bar+8*(B_PAR+w));
      }
      if(elect_one()){
        const int orow = pos2row(w*1024+rt*64+53);
        #pragma unroll
        for(int c=0;c<HF;c++){
          mbar_wait(bar+8*(B_XEMPTY+w*NX+c), 1);
          tma4d_red_add(&maps.out8, rank*256+((fp+c)&3)*64, orow&7, (orow>>3)&15, orow>>7, sb+OFF_X+(w*NX+c)*XSLOT);
        }
        asm volatile("cp.async.bulk.commit_group;":::"memory");
        asm volatile("cp.async.bulk.wait_group.read 0;":::"memory");
      }
      __syncwarp();
    }
  } else {
    if(elect_one()){
      mbar_init(bar+8*(B_Q+warp),1);
      asm volatile("fence.proxy.async.shared::cta;":::"memory");
      mbar_expect_tx(bar+8*(B_Q+warp), 2048);
      const bf16* qp = q + pos2row((1-wg)*1024+b*8+(warp&3)*2)*512;
      bulk_g2s(sb+OFF_Q+2*warp*QP, qp, 1024, bar+8*(B_Q+warp)); bulk_g2s(sb+OFF_Q+(2*warp+1)*QP, qp-16*512, 1024, bar+8*(B_Q+warp));
    }
    __syncwarp();
    asm volatile("setmaxnreg.inc.sync.aligned.u32 224;");
    if(elect_one()){
      mbar_init(bar+8*(B_U+warp),1); mbar_expect_tx(bar+8*(B_U+warp), 2048);
      mbar_init(bar+8*(B_XFULL+warp),1); mbar_init(bar+8*(B_XEMPTY+warp),8);
      mbar_init(bar+8*(B_KV+warp),1);
      if(warp<NS){ mbar_init(bar+8*(B_WFULL+warp),1); mbar_init(bar+8*(B_WEMPTY+warp),8); mbar_init(bar+8*(B_ONE+warp),1); }
      else { const int i=warp-6; mbar_init(bar+8*(B_PRDY+i),4); mbar_init(bar+8*(B_RT+i),1); mbar_init(bar+8*(B_AFULL+i),1); mbar_expect_tx(bar+8*(B_AFULL+i), 22528); mbar_init(bar+8*(B_PAR+i),2); mbar_init(bar+8*(B_HD+i),8+i); if(i){ mbar_init(bar+8*B_SC,1); mbar_init(bar+8*B_X03,1); } else { mbar_init(bar+8*B_QD,8); mbar_init(bar+8*B_TD,3); } }
      asm volatile("fence.mbarrier_init.release.cluster;":::"memory");
    }
    __syncwarp();
    const int wq = warp&3, g = lane>>2, t = lane&3;
    if(tid<8){ sts128(sb+OFF_U+tid*UPL+128*16, 0,0,0,0); }
    if(tid<128) sts128(sb+OFF_ZB+tid*16, 0,0,0,0);
    if(tid<12){ sts128(sb+OFF_TBL+(tid&3)*TBL+(tid>>2)*16, 0,0,0,0); }
    uint4 kq[4]; uint32_t kn[4];
    #pragma unroll
    for(int i=0;i<4;i++){ kq[i]=ldg_nc128(ssmk+(b*4+i)*2048+tid*8); kn[i]=0; if(lane==31 && warp<7) asm volatile("ld.global.nc.u32 %0, [%1];":"=r"(kn[i]):"l"(ssmk+(b*4+i)*2048+tid*8+8)); }
    asm volatile("bar.sync 0;":::"memory");
    asm volatile("barrier.cluster.arrive.relaxed.aligned;":::"memory");
    #pragma unroll
    for(int i=0;i<4;i++) mbar_wait(bar+8*(B_Q+wg*4+i), 0);
    {
      const uint32_t la = sb+OFF_Q+(wg*8+2*(lane>>3)+(lane&1))*QP + ((lane&7)>>1)*16 + wq*256;
      uint4 tv[4];
      const int irow = wq*32+t*2+(g>>2);
      const uint32_t dst = sb+OFF_IMG+irow*128+(((((g&3)+4*wg)^(b&7))^(irow&7))<<4);
      #pragma unroll
      for(int i=0;i<4;i++) ldsm4t(la+i*64, tv[i].x,tv[i].y,tv[i].z,tv[i].w);
      #pragma unroll
      for(int i=0;i<4;i++) sts128(dst+i*1024, max(~tv[i].x,1u),tv[i].y,tv[i].z,tv[i].w);
      asm volatile("fence.proxy.async.shared::cta;":::"memory");
      __syncwarp();
      if(lane==0) mbar_arrive(bar+8*B_QD);
    }
    {
      uint32_t w[2][8];
      const uint32_t qa = sb+OFF_Q+(2*warp)*QP+lane*16;
      #pragma unroll
      for(int r=0;r<2;r++){ lds128_nm(qa+r*QP, w[r][0],w[r][1],w[r][2],w[r][3]); lds128_nm(qa+r*QP+512, w[r][4],w[r][5],w[r][6],w[r][7]); }
      float s[2], d[2];
      #pragma unroll
      for(int r=0;r<2;r++){
        float s0=0.f,s1=0.f,d0=0.f,d1=0.f;
        #pragma unroll
        for(int i=0;i<8;i++){ const float lo=bf_lo(w[r][i]), hi=bf_hi(w[r][i]); s0+=lo; s1+=hi; d0=fmaf(lo,lo,d0); d1=fmaf(hi,hi,d1); }
        s[r]=s0+s1; d[r]=d0+d1;
      }
      const bool u=lane&16, v=lane&8;
      const float a0=(u? s[1]:s[0])+__shfl_xor_sync(~0u,u? s[0]:s[1],16), a1=(u? d[1]:d[0])+__shfl_xor_sync(~0u,u? d[0]:d[1],16);
      float c0=(v? a1:a0)+__shfl_xor_sync(~0u,v? a0:a1,8);
      c0+=__shfl_xor_sync(~0u,c0,4); c0+=__shfl_xor_sync(~0u,c0,2); c0+=__shfl_xor_sync(~0u,c0,1);
      const float m=c0*(1.f/512), sq=__shfl_down_sync(~0u,c0,8);
      const float rs=ln_rstd(fmaxf(fmaf(-m,m,sq*(1.f/512)),0.f)), rh=rbf(rs);
      const float m1=__shfl_down_sync(~0u,m,16), rs1=__shfl_down_sync(~0u,rs,16), rh1=rbf(rs1);
      mbar_wait(bar+8*B_SC, 0);
      if(lane==0){ st_rlx128(&g_qs[b*8+(warp^(b&7))], pack_bf16(m,m1), pack_bf16(rh,rh1), pack_bf16(rs-rh,rs1-rh1), lds32(sb+OFF_MISC)); }
      __syncwarp();
    }
    mbar_wait(bar+8*B_SC, 0);
    {
      const int Q = tid+2;
      const uint32_t ta = sb+OFF_TBL+((Q*32)^(((Q>>2)&3)<<5));
      const bool sw2 = (Q>>2)&1;
      if(tid==0){
        const uint32_t d01=lds32(sb+OFF_MISC+4), d23=lds32(sb+OFF_MISC+8);
        kq[0].x=hadd2_bf16(kq[0].x,d01&0xffffu); kq[1].x=hadd2_bf16(kq[1].x,d01>>16); kq[2].x=hadd2_bf16(kq[2].x,d23&0xffffu); kq[3].x=hadd2_bf16(kq[3].x,d23>>16);
      }
      __syncwarp();
      #pragma unroll
      for(int i=0;i<4;i++){
        uint32_t nx = __shfl_down_sync(~0u, kq[i].x, 1); if(lane==31) nx = kn[i];
        const uint4 o = make_uint4(__byte_perm(kq[i].x,kq[i].y,0x5432), __byte_perm(kq[i].y,kq[i].z,0x5432), __byte_perm(kq[i].z,kq[i].w,0x5432), __byte_perm(kq[i].w,nx,0x5432));
        const uint4 f0 = sw2? o:kq[i], f1 = sw2? kq[i]:o;
        sts128(ta+i*TBL+(sw2?16:0), f0.x,f0.y,f0.z,f0.w);
        sts128(ta+i*TBL+(sw2?0:16), f1.x,f1.y,f1.z,f1.w);
        if(tid==0) sts128(sb+OFF_TBL+i*TBL+48, 0,0,0, kq[i].x<<16);
      }
      __syncwarp();
      asm volatile("bar.sync 1, 256;":::"memory");
    }
    __syncwarp();
    if(lane<3) mbar_arrive(bar+8*(B_WEMPTY+(lane==2? 4:lane)));
    asm volatile("barrier.cluster.wait.aligned;":::"memory");
    bool x_ok = false;
    {
      const int c=lane>>3, p=g&1;
      uint32_t tb[5];
      #pragma unroll
      for(int s=0;s<5;s++){ const int y=16*c+wq+t+p+4*s; const int id=8*(y>>2)+4*(1-p)+(y&3); tb[s]=sb+OFF_TBL+wg*2*TBL+((id^(((id>>5)&3)<<3))<<2); }
      uint64_t du = make_desc(sb+OFF_U+wg*2*UCH, UPL, 128, 0);
      float aE[2][32], aL[2][32];
      uint32_t R[2][4][8], oku=0; uint4 xr[4], st[8], ar[2], e0;
#define P_TY(K) ((K)>=8 ? 2 : (K)&1)
#define P_LV(K) ((K)>=8 ? (K)-8 : (K)>>1)
#define P_MA(K) ((P_TY(K)==1 ? 15 : 7) - 2*P_LV(K))
#define P_N(K,M) (P_TY(K)==2 ? 64 : P_TY(K)==1 ? 128-8*(M) : 64-8*(M))
#define P_B(K,M) (8*(M) + (P_TY(K)==0 ? 64 : 0))
#define P_LD(K,J) conv_lda(R[(K)&1][J],tb,((J)&1)*TBL+(P_MA(K)-((J)>>1))*512)
#define P_MMA(K,J) conv_mma<P_N(K,P_MA(K)-((J)>>1))>(P_TY(K)==0? aE[(J)&1]:aL[(J)&1], R[(K)&1][J], du+((J)&1)*(UCH/16)+P_B(K,P_MA(K)-((J)>>1)))
#define CONV_PREP(K) { if constexpr(P_TY(K)!=1) oku = mbar_test(bar+8*(B_U+P_LV(K)+(P_TY(K)?4:0)),0); P_LD(K,0); P_LD(K,1); P_LD(K,2); P_LD(K,3); }
#define CONV_PAIR(K) { \
        _Pragma("unroll") for(int j=0;j<4;j++) conv_dup(R[(K)&1][j]); \
        if constexpr(P_TY(K)<2){ _Pragma("unroll") for(int i=0;i<2;i++){ float* a_=(P_TY(K)==0? aE[i]:aL[i])+8*P_LV(K); zero4(a_); zero4(a_+4); } } \
        if constexpr(P_TY(K)!=1){ if(!oku) mbar_wait(bar+8*(B_U+P_LV(K)+(P_TY(K)?4:0)),0); asm volatile("fence.proxy.async.shared::cta;":::"memory"); } \
        asm volatile("" : "+l"(du)); \
        PP_SYNC(); \
        wg_fence(); \
        P_MMA(K,0); P_MMA(K,1); \
        if constexpr(P_TY(K)<2){ wg_commit(); wg_fence(); } \
        P_MMA(K,2); P_MMA(K,3); \
        wg_commit(); \
        if((K)<11 || wg==0) PP_ARRIVE(); \
        if constexpr((K)<11){ if constexpr((K)>0){ if constexpr(P_TY(K)<2) wg_wait<2>(); else wg_wait<1>(); } if constexpr((K)!=6 && (K)!=0) CONV_PREP((K)+1) } }
#define PP_SYNC() asm volatile("bar.sync %0, 256;"::"r"(2+wg):"memory")
#define PP_ARRIVE() asm volatile("bar.arrive %0, 256;"::"r"(3-wg):"memory")
      if(wg==1) PP_ARRIVE();
      CONV_PREP(0) CONV_PREP(1) CONV_PAIR(0) CONV_PAIR(1) CONV_PAIR(2) CONV_PAIR(3) CONV_PAIR(4) CONV_PAIR(5)
      mbar_wait(bar+8*B_XA,0);
      wg_wait<0>();
      load_xs(xr,st,sb,warp,lane); check_xs(xr,st,lds32(sb+OFF_MISC),sb,warp); ln_x(xr+2,st+4,ar);
      if(lane==0) mbar_arrive(bar+8*(B_WEMPTY+3));
      CONV_PAIR(6)
      if(lane==0) mbar_arrive(bar+8*(B_WEMPTY+2));
      wg_wait<0>();
      conv_put<1>(aE[0],aE[1],e0,sb,warp,lane);
      CONV_PREP(7)
      conv_get<1>(xr+2,ar,sb,warp,lane);
      __syncwarp();
      if(lane==0) mbar_arrive(bar+8*B_HD);
      CONV_PAIR(7) CONV_PAIR(8) CONV_PAIR(9) CONV_PAIR(10) CONV_PAIR(11)
      ln_x(xr,st,ar);
      if(wg==0 && mbar_test(bar+8*B_XFULL, 0)) x_ok = !x_bad(sb, 0, wq, lane);
      wg_wait<0>();
      conv_put<0>(aL[0],aL[1],e0,sb,warp,lane);
      conv_get<0>(xr,ar,sb,warp,lane);
      __syncwarp();
      if(lane==0){ mbar_arrive(bar+8*(B_HD+1)); mbar_arrive(bar+8*(B_WEMPTY+5)); }
    }
    if(wg==1 && wq<3){
      mbar_wait(bar+8*(B_WFULL+SKW+(rt&1)), 0);
      const int j = tid-128;
      const uint32_t par = lds32(sb+OFF_MISC)&1;
      float c0=0.f,c1=0.f,c2=0.f,c3=0.f;
      const uint32_t cb = sb+OFF_W+(5-SKW-(rt&1))*WSLOT+wq*8192+t*4+maps.upfirst*4096;
      #pragma unroll CSU
      for(int k=0;k<32;k++){
        const uint32_t ad = cb + k*128 + ((g^(k&7))<<4);
        const uint32_t v=lds32(ad), u=lds32(ad+4096-maps.upfirst*8192); c0+=bf_lo(v); c1+=bf_hi(v); c2+=bf_lo(u); c3+=bf_hi(u);
      }
      if(j<88) st_rlx128(&g_csp[(f*16+rt)*88+j], (__float_as_uint(c0)&~1u)|par, __float_as_uint(c1), __float_as_uint(c2), __float_as_uint(c3));
      __syncwarp();
    }
    const uint32_t xempty_cl = mapa(bar+8*(B_XEMPTY+wg*NX), lane&1);
    float ag[88], au[88];
    const uint32_t xbase = sb+OFF_X+wg*NX*XSLOT, rbase = sb+(wg? OFF_RES1:OFF_RES0);
    const uint32_t rfrag = rbase+((lane&7)+8*(lane>>4))*128+(((2*wq+((lane>>3)&1))^(lane&7))<<4);
    constexpr uint64_t DHI_A = (uint64_t)0x40000040u<<32, DHI_B = DHI_A | (512u<<16);
    const uint32_t og = maps.upfirst*256, ou = 256-og;
    uint32_t wb = bar+8*wg*(SKW%NS), ph = wg*(SKW/NS), dbl = (((sb+OFF_W+(5-wg*(SKW%NS))*WSLOT)&0x3FFFF)>>4), dal = (xbase&0x3FFFF)>>4, xb = bar+8*(B_XFULL+wg*NX), pwb = 0;
    uint32_t relm = lane==0? 0xff : lane==1? (wg? (0xff00>>(SKW/2))&0xff : (1<<(SKW/2))-1) : 0;
#define G1_STAGE(DA,DB,ACC) { wg_fence(); wgmma_ss<176,1,1>(ag, DA, DHI_B|((DB)+og), ACC); wgmma_ss<176,1,1>(au, DA, DHI_B|((DB)+ou), ACC); wgmma_ss<176,1,1>(ag, (DA)+128, DHI_B|((DB)+og+128), 1); wgmma_ss<176,1,1>(au, (DA)+128, DHI_B|((DB)+ou+128), 1); wg_commit(); }
    {
      mbar_wait(wb, ph);
      if(!x_ok){
        mbar_wait(xb, 0);
        if(x_bad(sb, wg, wq, lane)){
          const uint32_t par = lds32(sb+OFF_MISC), co = lane*128+(((2*wq)^(lane&7))<<4);
          #pragma unroll 1
          for(int tl=0;tl<4;tl++){
            const bf16* src = g_hT+((tl<3? ((rt>>1)+wg*(SKW/2)+tl)&7 : rank*4+fp)*64+lane)*2048+wg*1024+rt*64+wq*16;
            uint4 v[4]; int n=0;
            do{
              #pragma unroll
              for(int i=0;i<4;i++) ld_rlx128(src+(i>>1)*32*2048+(i&1)*8, v[i]);
            }while((((v[0].x^par)|(v[1].x^par)|(v[2].x^par)|(v[3].x^par))&1) && ++n<2000000);
            #pragma unroll
            for(int i=0;i<4;i++) sts128(((tl<3? xbase+tl*8192 : rbase)+(i>>1)*4096+co)^((i&1)<<4), v[i].x,v[i].y,v[i].z,v[i].w);
          }
          asm volatile("fence.proxy.async.shared::cta;":::"memory");
          __syncwarp();
        }
      }
      #pragma unroll
      for(int i=0;i<88;i++){ ag[i]=0.f; au[i]=0.f; }
      G1_STAGE(DHI_A|dal, dbl, 0)
    }
    uint32_t okb = mbar_test(wb+8, ph);
    #pragma unroll 1
    for(int xi=0; xi<8; xi++){
      if(!okb) mbar_wait(wb+8, ph);
      G1_STAGE(DHI_A|(dal+256), dbl-WSLOT/16, 1)
      pwb = wb;
      const bool wrap = wb==bar+8*4;
      wb = wrap? bar : wb+16; dbl = wrap? dbl+4*(WSLOT/16) : dbl-2*(WSLOT/16); ph ^= wrap;
      dal = (xi==3)? dal-3*512 : dal+512; xb = (xi==3)? xb-24 : xb+8;
      const uint32_t oka = mbar_test(xb, xi>=3) & mbar_test(wb, ph);
      if(xi==(wg? STX1:STX0)){
        float s0=0.f,s1=0.f,q0=0.f,q1=0.f;
        #pragma unroll
        for(int kk=0;kk<4;kk++){
          uint32_t r[4]; ldsm4t(rfrag+kk*2048, r[0],r[1],r[2],r[3]);
          #pragma unroll
          for(int i=0;i<4;i++){ const float lo=bf_lo(r[i]), hi=bf_hi(r[i]); if(i&1){ s1+=lo+hi; q1=fmaf(lo,lo,fmaf(hi,hi,q1)); } else { s0+=lo+hi; q0=fmaf(lo,lo,fmaf(hi,hi,q0)); } }
        }
        #pragma unroll
        for(int o=1;o<4;o<<=1){ s0+=__shfl_xor_sync(~0u,s0,o); q0+=__shfl_xor_sync(~0u,q0,o); s1+=__shfl_xor_sync(~0u,s1,o); q1+=__shfl_xor_sync(~0u,q1,o); }
        if(t==0) st_rlx128(&g_stat[((rt*2+wg)*8+f)*32+wq*8+g], (__float_as_uint(s0)&~1u)|(lds32(sb+OFF_MISC)&1), __float_as_uint(q0), __float_as_uint(s1), __float_as_uint(q1));
        __syncwarp();
        if(tid==wg*128) mbar_arrive(bar+8*(B_RT+wg));
      }
      uint32_t rel = relm&1; relm>>=1; uint32_t xpar = xi>=3;
      asm volatile("":"+r"(rel),"+r"(xpar));
      wg_wait<1>();
      if(rel) mbar_arrive(pwb+8*B_WEMPTY);
      if(xi==7) break;
      if(!oka){ mbar_wait(xb, xpar); mbar_wait(wb, ph); }
      G1_STAGE(DHI_A|dal, dbl, 1)
      okb = mbar_test(wb+8, ph);
      wg_wait<1>();
      if(rel) mbar_arrive(pwb+8*B_WEMPTY+8);
      if((lane>>1)==1 && xi<4) mbar_arrive_cl(xempty_cl+8*xi);
      if(xi==6 && lane==0) mbar_arrive_cl(mapa(bar+8*(B_PRDY+wg), rank^1));
    }
    mbar_wait(bar+8*(B_PAR+wg), 0);
    mbar_wait(bar+8*(B_PRDY+wg), 0);
    const float4 p0=*(const float4*)(smem_raw+OFF_ROW+(wg*32+wq*8+g)*16);
    const float nm0=p0.x, r0=p0.y, nm1=p0.z, r1=p0.w;
    wg_wait<0>();
    if(lane==0){ mbar_arrive_n(pwb+8*B_WEMPTY+8, (wg && SKW)? 2:1); }
    uint32_t act[44], actp[44];
    const float sc0=0.5f*r0*r0, sc1=0.5f*r1*r1;
    const uint32_t adst = mapa(xbase+(3-wq)*2048+lane*16, rank^1), abar = mapa(bar+8*(B_AFULL+wg), rank^1);
    {
      const float4* cs = (const float4*)(smem_raw+OFF_CS);
      const float h0=0.5f*r0, h1=0.5f*r1;
      #pragma unroll
      for(int j=0;j<22;j++){
        const float4 c4=cs[4*j+t];
        const float g0=fmaf(nm0,c4.x,ag[4*j+0]), g1=fmaf(nm0,c4.y,ag[4*j+1]), g2=fmaf(nm1,c4.x,ag[4*j+2]), g3=fmaf(nm1,c4.y,ag[4*j+3]);
        const float y0=g0*fmaf(nm0,c4.z,au[4*j+0]), y1=g1*fmaf(nm0,c4.w,au[4*j+1]), y2=g2*fmaf(nm1,c4.z,au[4*j+2]), y3=g3*fmaf(nm1,c4.w,au[4*j+3]);
        act[2*j]  =pack_bf16(y0*fmaf(sc0,tanh_fast(g0*h0),sc0), y1*fmaf(sc0,tanh_fast(g1*h0),sc0));
        act[2*j+1]=pack_bf16(y2*fmaf(sc1,tanh_fast(g2*h1),sc1), y3*fmaf(sc1,tanh_fast(g3*h1),sc1));
        if((j%3)==2 && j/3<NIN){ const int kk=j/3; st_async128(adst+(kk>>2)*8192+(kk&3)*512, act[4*kk],act[4*kk+1],act[4*kk+2],act[4*kk+3], abar); }
      }
    }
    #pragma unroll
    for(int kk=NIN;kk<11;kk++) st_async128(adst+(kk>>2)*8192+(kk&3)*512, act[4*kk],act[4*kk+1],act[4*kk+2],act[4*kk+3], abar);
    float acc2[2][32];
    #pragma unroll
    for(int i=0;i<32;i++){ acc2[0][i]=0.f; acc2[1][i]=0.f; }
    const uint32_t wbase = xbase+(3-wq)*2048;
    const uint32_t srow = ((~lane&4)<<1) | ((~lane&1)<<2) | (lane&2) | ((lane>>3)&1);
    const int orow = pos2row(wg*1024+rt*64+wq*16+5);
    uint32_t hr[16];
    #pragma unroll
    for(int kk=0;kk<4;kk++) ldsm4t(rfrag+kk*2048, hr[4*kk],hr[4*kk+1],hr[4*kk+2],hr[4*kk+3]);
    auto stage=[&](const float* a, int c){
      #pragma unroll
      for(int kk=0;kk<4;kk++){
        uint32_t o0=pack_bf16(a[8*kk],a[8*kk+1]), o1=pack_bf16(a[8*kk+2],a[8*kk+3]), o2=pack_bf16(a[8*kk+4],a[8*kk+5]), o3=pack_bf16(a[8*kk+6],a[8*kk+7]);
        if(c==0){
          o0=hadd2_bf16(o0,hr[4*kk]); o1=hadd2_bf16(o1,hr[4*kk+1]); o2=hadd2_bf16(o2,hr[4*kk+2]); o3=hadd2_bf16(o3,hr[4*kk+3]);
        }
        stsm4_nm(wbase+c*8192+srow*128+(((2*kk+(lane>>4))^(srow&7))<<4), o0,o1,o2,o3);
      }
    };
    auto flush=[&](int c, int n){
      asm volatile("fence.proxy.async.shared::cta;":::"memory");
      __syncwarp();
      if(c<HF){ if(lane<2) mbar_arrive(bar+8*(B_XEMPTY+wg*NX+c)); }
      else if(elect_one()){
        tma4d_red_add(&maps.out, rank*256+((fp+c)&3)*64, orow&7, (orow>>3)&15, orow>>7, wbase+c*8192);
        asm volatile("cp.async.bulk.commit_group;":::"memory");
      }
    };
    uint32_t okw = 0;
    #pragma unroll
    for(int i=0;i<8;i++){
      const int ch = (G2_CH>>(4*i))&3, peer = (G2_PEER>>i)&1;
      constexpr int S0=(16+SKW)%NS, P0=((16+SKW)/NS)&1;
      const int slot=(S0+i)%NS, pslot=(S0+i+NS-1)%NS, ph=(P0+(S0+i)/NS)&1;
      if(i==2){
        mbar_wait(bar+8*(B_AFULL+wg), 0);
        #pragma unroll
        for(int kk=0;kk<11;kk++) lds128_nm(wbase+lane*16+(kk>>2)*8192+(kk&3)*512, actp[4*kk],actp[4*kk+1],actp[4*kk+2],actp[4*kk+3]);
      }
      if(!okw) mbar_wait(bar+8*(B_WFULL+slot), ph);
      if(i<7) okw = mbar_test(bar+8*(B_WFULL+(S0+i+1)%NS), (P0+(S0+i+1)/NS)&1);
      if(i==2 || i==4 || i==6 || (i==0 && wg==1)) asm volatile("bar.sync %0, 256;"::"r"(2+wg):"memory");
      const uint64_t db = make_desc(sb+OFF_W+(5-slot)*WSLOT, 0, 1024, 1);
      wg_fence();
      #pragma unroll
      for(int kk=0;kk<11;kk++){
        if(peer) wgmma_rs<64,1>(acc2[ch&1], actp[4*kk],actp[4*kk+1],actp[4*kk+2],actp[4*kk+3], db+kk*128, 1);
        else     wgmma_rs<64,1>(acc2[ch&1], act[4*kk],act[4*kk+1],act[4*kk+2],act[4*kk+3], db+kk*128, kk>0);
      }
      wg_commit();
      if(i==1 || i==3 || i==5 || (i==7 && wg==0)) asm volatile("bar.arrive %0, 256;"::"r"(3-wg):"memory");
      if(i==1){ wg_wait<0>(); if(lane<2) mbar_arrive(bar+8*(B_WEMPTY+(lane? slot:pslot))); }
      if(i==3){ wg_wait<1>(); stage(acc2[0], 0); flush(0,1); wg_wait<0>(); stage(acc2[1], 1); flush(1,1); }
      if(i==5){ wg_wait<0>(); stage(acc2[0], 2); flush(2,1); }
    }
    wg_wait<0>();
    stage(acc2[1], 3); flush(3,1);
    asm volatile("cp.async.bulk.wait_group.read 0;":::"memory");
  }
}

__device__ bf16 g_fb[S_*F_+2*S_*D_];
__device__ __forceinline__ float b2f_(bf16 x){ return __bfloat162float(x); }
__global__ void fb_ln(const bf16* x, bf16* y){
  __shared__ float red[16]; const int r=blockIdx.x, t=threadIdx.x; const float v=b2f_(x[r*512+t]);
  float s=v; for(int o=16;o;o>>=1) s+=__shfl_xor_sync(~0u,s,o); if((t&31)==0) red[t>>5]=s; __syncthreads(); s=0; for(int i=0;i<16;i++) s+=red[i]; const float m=s/512; __syncthreads();
  float d=(v-m)*(v-m); for(int o=16;o;o>>=1) d+=__shfl_xor_sync(~0u,d,o); if((t&31)==0) red[t>>5]=d; __syncthreads(); d=0; for(int i=0;i<16;i++) d+=red[i];
  y[r*512+t]=__float2bfloat16(rbf(v-rbf(m))/rbf(sqrtf(rbf(rbf(d/512)+1e-5f)))); }
__global__ void fb_kv(const bf16* k, const bf16* v, const bf16* sh, bf16* kv){ const int s=blockIdx.x, d=threadIdx.x; float a=0;
  for(int t=0;t<4;t++){ const int r=s+t-3; a=rbf(a+rbf((r>=0? b2f_(k[r*512+d]):0.f)*b2f_(sh[d*4+3-t]))); } kv[s*512+d]=__float2bfloat16(a*b2f_(v[s*512+d])); }
__global__ void fb_conv(const bf16* x, const bf16* qn, const bf16* kv, const bf16* K, const bf16* Dv, bf16* h){ const int s=blockIdx.x, d=threadIdx.x; float a=0;
  for(int j=0;j<=s;j++) a+=b2f_(K[d*2048+j])*b2f_(kv[(s-j)*512+d]);
  h[s*512+d]=__float2bfloat16(b2f_(x[s*512+d])+rbf(b2f_(qn[s*512+d])*rbf(rbf(a)+rbf(b2f_(kv[s*512+d])*b2f_(Dv[d]))))); }
__global__ void fb_g1(const bf16* xn, const bf16* wg, const bf16* wu, bf16* act){ const int s=blockIdx.x;
  for(int n=threadIdx.x;n<F_;n+=blockDim.x){ float g=0,u=0; for(int k=0;k<512;k++){ const float x=b2f_(xn[s*512+k]); g+=x*b2f_(wg[k*F_+n]); u+=x*b2f_(wu[k*F_+n]); }
    g=rbf(g); act[s*F_+n]=__float2bfloat16(rbf(g/(1.f+expf(-g)))*rbf(u)); } }
__global__ void fb_g2(const bf16* act, const bf16* wd, const bf16* h, bf16* out){ const int s=blockIdx.x, n=threadIdx.x; float a=0;
  for(int k=0;k<F_;k++) a+=b2f_(act[s*F_+k])*b2f_(wd[k*512+n]); out[s*512+n]=__float2bfloat16(b2f_(h[s*512+n])+rbf(a)); }

typedef CUresult (*PFN_encodeTiled)(CUtensorMap*, CUtensorMapDataType, cuuint32_t, void*, const cuuint64_t*, const cuuint64_t*, const cuuint32_t*, const cuuint32_t*, CUtensorMapInterleave, CUtensorMapSwizzle, CUtensorMapL2promotion, CUtensorMapFloatOOBfill);
static int g_enc_err;
static void make2d(PFN_encodeTiled enc, CUtensorMap* m, const void* p, uint64_t d0, uint64_t d1, uint32_t b0, uint32_t b1){
  cuuint64_t gd[2]={d0,d1}; cuuint64_t gs[1]={d0*2}; cuuint32_t bx[2]={b0,b1}; cuuint32_t es[2]={1,1};
  g_enc_err |= (int)enc(m,CU_TENSOR_MAP_DATA_TYPE_BFLOAT16,2,(void*)p,gd,gs,bx,es,CU_TENSOR_MAP_INTERLEAVE_NONE,CU_TENSOR_MAP_SWIZZLE_128B,CU_TENSOR_MAP_L2_PROMOTION_L2_128B,CU_TENSOR_MAP_FLOAT_OOB_FILL_NONE);
}
static void make3d(PFN_encodeTiled enc, CUtensorMap* m, const void* p, uint64_t d0, uint64_t d1, uint64_t d2, uint64_t s1, uint64_t s2, uint32_t b0, uint32_t b1, uint32_t b2, CUtensorMapSwizzle sw, CUtensorMapL2promotion pr){
  cuuint64_t gd[3]={d0,d1,d2}; cuuint64_t gs[2]={s1,s2}; cuuint32_t bx[3]={b0,b1,b2}; cuuint32_t es[3]={1,1,1};
  g_enc_err |= (int)enc(m,CU_TENSOR_MAP_DATA_TYPE_BFLOAT16,3,(void*)p,gd,gs,bx,es,CU_TENSOR_MAP_INTERLEAVE_NONE,sw,pr,CU_TENSOR_MAP_FLOAT_OOB_FILL_NONE);
}

extern "C" void kernel_launch(void* const* d_in, const int* in_sizes, int n_in, void* d_out, int out_size){
  const bf16* q=(const bf16*)d_in[0]; const bf16* k=(const bf16*)d_in[1]; const bf16* v=(const bf16*)d_in[2];
  const bf16* sh=(const bf16*)d_in[3]; const bf16* K=(const bf16*)d_in[4]; const bf16* Dv=(const bf16*)d_in[5];
  const bf16* wgt=(const bf16*)d_in[7]; const bf16* wup=(const bf16*)d_in[8]; const bf16* wdn=(const bf16*)d_in[9];
  void* fn=nullptr; cudaDriverEntryPointQueryResult qr; cudaGetDriverEntryPoint("cuTensorMapEncodeTiled",&fn,cudaEnableDefault,&qr);
  PFN_encodeTiled enc=(PFN_encodeTiled)fn;
  void* hT; cudaGetSymbolAddress(&hT,g_hT);
  Maps maps; g_enc_err = 0;
  make3d(enc,&maps.k,k,512,256,8,8192,1024,8,17,8,CU_TENSOR_MAP_SWIZZLE_NONE,CU_TENSOR_MAP_L2_PROMOTION_L2_128B);
  make3d(enc,&maps.v,v,512,256,8,8192,1024,8,16,8,CU_TENSOR_MAP_SWIZZLE_NONE,CU_TENSOR_MAP_L2_PROMOTION_L2_128B);
  { maps.upfirst = wup<wgt; const bf16* w0 = wup<wgt? wup:wgt; const uint64_t dm = (uint64_t)((wup<wgt? wgt-wup : wup-wgt)*2);
    cuuint64_t gd[4]={F_,D_,2,2}; cuuint64_t gs[3]={F_*2,dm,128}; cuuint32_t bx[4]={64,32,2,2}; cuuint32_t es[4]={1,1,1,1};
    g_enc_err |= (int)enc(&maps.w64,CU_TENSOR_MAP_DATA_TYPE_BFLOAT16,4,(void*)w0,gd,gs,bx,es,CU_TENSOR_MAP_INTERLEAVE_NONE,CU_TENSOR_MAP_SWIZZLE_128B,CU_TENSOR_MAP_L2_PROMOTION_L2_128B,CU_TENSOR_MAP_FLOAT_OOB_FILL_NONE);
    make3d(enc,&maps.w48,w0,F_,D_,2,F_*2,dm,48,32,2,CU_TENSOR_MAP_SWIZZLE_128B,CU_TENSOR_MAP_L2_PROMOTION_L2_128B); }
  make2d(enc,&maps.wd,wdn,D_,F_,64,176);
  make2d(enc,&maps.ht,hT,S_,D_,64,32);
  { cuuint64_t gd[4]={512,8,16,16}; cuuint64_t gs[3]={1024,8192,131072}; cuuint32_t bx[4]={64,2,4,2}; cuuint32_t es[4]={1,1,1,1};
    g_enc_err |= (int)enc(&maps.out,CU_TENSOR_MAP_DATA_TYPE_BFLOAT16,4,d_out,gd,gs,bx,es,CU_TENSOR_MAP_INTERLEAVE_NONE,CU_TENSOR_MAP_SWIZZLE_128B,CU_TENSOR_MAP_L2_PROMOTION_NONE,CU_TENSOR_MAP_FLOAT_OOB_FILL_NONE);
    bx[3]=8; g_enc_err |= (int)enc(&maps.out8,CU_TENSOR_MAP_DATA_TYPE_BFLOAT16,4,d_out,gd,gs,bx,es,CU_TENSOR_MAP_INTERLEAVE_NONE,CU_TENSOR_MAP_SWIZZLE_128B,CU_TENSOR_MAP_L2_PROMOTION_NONE,CU_TENSOR_MAP_FLOAT_OOB_FILL_NONE); }
  void* xa; cudaGetSymbolAddress(&xa,g_xa);
  make2d(enc,&maps.xa,xa,8192,128,64,128);
  cudaFuncSetAttribute(fused_kernel,cudaFuncAttributeMaxDynamicSharedMemorySize,SMEM_BYTES);
  int ncl = 0;
  { cudaLaunchConfig_t cfg = {}; cfg.gridDim = dim3(128); cfg.blockDim = dim3(384); cfg.dynamicSmemBytes = SMEM_BYTES;
    cudaLaunchAttribute at[1]; at[0].id = cudaLaunchAttributeClusterDimension; at[0].val.clusterDim.x = 2; at[0].val.clusterDim.y = 1; at[0].val.clusterDim.z = 1;
    cfg.attrs = at; cfg.numAttrs = 1;
    if(cudaOccupancyMaxActiveClusters(&ncl, fused_kernel, &cfg) != cudaSuccess){ ncl = 0; (void)cudaGetLastError(); } }
  if(g_enc_err || ncl < 64){
    bf16* fb; cudaGetSymbolAddress((void**)&fb, g_fb); bf16 *ln=fb, *kv=fb+S_*D_, *act=fb+2*S_*D_;
    fb_ln<<<S_,512>>>(q,ln); fb_kv<<<S_,512>>>(k,v,sh,kv); fb_conv<<<S_,512>>>(q,ln,kv,K,Dv,(bf16*)hT); fb_ln<<<S_,512>>>((bf16*)hT,ln);
    fb_g1<<<S_,256>>>(ln,wgt,wup,act); fb_g2<<<S_,512>>>(act,wdn,(bf16*)hT,(bf16*)d_out);
    return;
  }
  fused_kernel<<<128,384,SMEM_BYTES>>>(maps,q,sh,K,Dv,wdn,(bf16*)d_out);
}
```

```cpp
#include <cuda_runtime.h>
#include <cuda_bf16.h>
#include <cuda.h>
#include <stdint.h>

template<int TA,int TB> __device__ __forceinline__ void wgmma_ss_n176(float* d, uint64_t da, uint64_t db, int sd){
  asm volatile("{ .reg .pred p; setp.ne.b32 p, %90, 0; wgmma.mma_async.sync.aligned.m64n176k16.f32.bf16.bf16 {%0,%1,%2,%3,%4,%5,%6,%7,%8,%9,%10,%11,%12,%13,%14,%15,%16,%17,%18,%19,%20,%21,%22,%23,%24,%25,%26,%27,%28,%29,%30,%31,%32,%33,%34,%35,%36,%37,%38,%39,%40,%41,%42,%43,%44,%45,%46,%47,%48,%49,%50,%51,%52,%53,%54,%55,%56,%57,%58,%59,%60,%61,%62,%63,%64,%65,%66,%67,%68,%69,%70,%71,%72,%73,%74,%75,%76,%77,%78,%79,%80,%81,%82,%83,%84,%85,%86,%87}, %88, %89, p, 1, 1, %91, %92; }"
   : "+f"(d[0]),"+f"(d[1]),"+f"(d[2]),"+f"(d[3]),"+f"(d[4]),"+f"(d[5]),"+f"(d[6]),"+f"(d[7]),"+f"(d[8]),"+f"(d[9]),"+f"(d[10]),"+f"(d[11]),"+f"(d[12]),"+f"(d[13]),"+f"(d[14]),"+f"(d[15]),"+f"(d[16]),"+f"(d[17]),"+f"(d[18]),"+f"(d[19]),"+f"(d[20]),"+f"(d[21]),"+f"(d[22]),"+f"(d[23]),"+f"(d[24]),"+f"(d[25]),"+f"(d[26]),"+f"(d[27]),"+f"(d[28]),"+f"(d[29]),"+f"(d[30]),"+f"(d[31]),"+f"(d[32]),"+f"(d[33]),"+f"(d[34]),"+f"(d[35]),"+f"(d[36]),"+f"(d[37]),"+f"(d[38]),"+f"(d[39]),"+f"(d[40]),"+f"(d[41]),"+f"(d[42]),"+f"(d[43]),"+f"(d[44]),"+f"(d[45]),"+f"(d[46]),"+f"(d[47]),"+f"(d[48]),"+f"(d[49]),"+f"(d[50]),"+f"(d[51]),"+f"(d[52]),"+f"(d[53]),"+f"(d[54]),"+f"(d[55]),"+f"(d[56]),"+f"(d[57]),"+f"(d[58]),"+f"(d[59]),"+f"(d[60]),"+f"(d[61]),"+f"(d[62]),"+f"(d[63]),"+f"(d[64]),"+f"(d[65]),"+f"(d[66]),"+f"(d[67]),"+f"(d[68]),"+f"(d[69]),"+f"(d[70]),"+f"(d[71]),"+f"(d[72]),"+f"(d[73]),"+f"(d[74]),"+f"(d[75]),"+f"(d[76]),"+f"(d[77]),"+f"(d[78]),"+f"(d[79]),"+f"(d[80]),"+f"(d[81]),"+f"(d[82]),"+f"(d[83]),"+f"(d[84]),"+f"(d[85]),"+f"(d[86]),"+f"(d[87]) : "l"(da), "l"(db), "r"(sd), "n"(TA), "n"(TB));
}
template<int TB> __device__ __forceinline__ void wgmma_rs_n8(float* d, uint32_t a0, uint32_t a1, uint32_t a2, uint32_t a3, uint64_t db, int sd){
  asm volatile("{ .reg .pred p; setp.ne.b32 p, %9, 0; wgmma.mma_async.sync.aligned.m64n8k16.f32.bf16.bf16 {%0,%1,%2,%3}, {%4,%5,%6,%7}, %8, p, 1, 1, %10; }"
   : "+f"(d[0]),"+f"(d[1]),"+f"(d[2]),"+f"(d[3]) : "r"(a0),"r"(a1),"r"(a2),"r"(a3), "l"(db), "r"(sd), "n"(TB));
}
template<int TB> __device__ __forceinline__ void wgmma_rs_n16(float* d, uint32_t a0, uint32_t a1, uint32_t a2, uint32_t a3, uint64_t db, int sd){
  asm volatile("{ .reg .pred p; setp.ne.b32 p, %13, 0; wgmma.mma_async.sync.aligned.m64n16k16.f32.bf16.bf16 {%0,%1,%2,%3,%4,%5,%6,%7}, {%8,%9,%10,%11}, %12, p, 1, 1, %14; }"
   : "+f"(d[0]),"+f"(d[1]),"+f"(d[2]),"+f"(d[3]),"+f"(d[4]),"+f"(d[5]),"+f"(d[6]),"+f"(d[7]) : "r"(a0),"r"(a1),"r"(a2),"r"(a3), "l"(db), "r"(sd), "n"(TB));
}
template<int TB> __device__ __forceinline__ void wgmma_rs_n24(float* d, uint32_t a0, uint32_t a1, uint32_t a2, uint32_t a3, uint64_t db, int sd){
  asm volatile("{ .reg .pred p; setp.ne.b32 p, %17, 0; wgmma.mma_async.sync.aligned.m64n24k16.f32.bf16.bf16 {%0,%1,%2,%3,%4,%5,%6,%7,%8,%9,%10,%11}, {%12,%13,%14,%15}, %16, p, 1, 1, %18; }"
   : "+f"(d[0]),"+f"(d[1]),"+f"(d[2]),"+f"(d[3]),"+f"(d[4]),"+f"(d[5]),"+f"(d[6]),"+f"(d[7]),"+f"(d[8]),"+f"(d[9]),"+f"(d[10]),"+f"(d[11]) : "r"(a0),"r"(a1),"r"(a2),"r"(a3), "l"(db), "r"(sd), "n"(TB));
}
template<int TB> __device__ __forceinline__ void wgmma_rs_n32(float* d, uint32_t a0, uint32_t a1, uint32_t a2, uint32_t a3, uint64_t db, int sd){
  asm volatile("{ .reg .pred p; setp.ne.b32 p, %21, 0; wgmma.mma_async.sync.aligned.m64n32k16.f32.bf16.bf16 {%0,%1,%2,%3,%4,%5,%6,%7,%8,%9,%10,%11,%12,%13,%14,%15}, {%16,%17,%18,%19}, %20, p, 1, 1, %22; }"
   : "+f"(d[0]),"+f"(d[1]),"+f"(d[2]),"+f"(d[3]),"+f"(d[4]),"+f"(d[5]),"+f"(d[6]),"+f"(d[7]),"+f"(d[8]),"+f"(d[9]),"+f"(d[10]),"+f"(d[11]),"+f"(d[12]),"+f"(d[13]),"+f"(d[14]),"+f"(d[15]) : "r"(a0),"r"(a1),"r"(a2),"r"(a3), "l"(db), "r"(sd), "n"(TB));
}
template<int TB> __device__ __forceinline__ void wgmma_rs_n40(float* d, uint32_t a0, uint32_t a1, uint32_t a2, uint32_t a3, uint64_t db, int sd){
  asm volatile("{ .reg .pred p; setp.ne.b32 p, %25, 0; wgmma.mma_async.sync.aligned.m64n40k16.f32.bf16.bf16 {%0,%1,%2,%3,%4,%5,%6,%7,%8,%9,%10,%11,%12,%13,%14,%15,%16,%17,%18,%19}, {%20,%21,%22,%23}, %24, p, 1, 1, %26; }"
   : "+f"(d[0]),"+f"(d[1]),"+f"(d[2]),"+f"(d[3]),"+f"(d[4]),"+f"(d[5]),"+f"(d[6]),"+f"(d[7]),"+f"(d[8]),"+f"(d[9]),"+f"(d[10]),"+f"(d[11]),"+f"(d[12]),"+f"(d[13]),"+f"(d[14]),"+f"(d[15]),"+f"(d[16]),"+f"(d[17]),"+f"(d[18]),"+f"(d[19]) : "r"(a0),"r"(a1),"r"(a2),"r"(a3), "l"(db), "r"(sd), "n"(TB));
}
template<int TB> __device__ __forceinline__ void wgmma_rs_n48(float* d, uint32_t a0, uint32_t a1, uint32_t a2, uint32_t a3, uint64_t db, int sd){
  asm volatile("{ .reg .pred p; setp.ne.b32 p, %29, 0; wgmma.mma_async.sync.aligned.m64n48k16.f32.bf16.bf16 {%0,%1,%2,%3,%4,%5,%6,%7,%8,%9,%10,%11,%12,%13,%14,%15,%16,%17,%18,%19,%20,%21,%22,%23}, {%24,%25,%26,%27}, %28, p, 1, 1, %30; }"
   : "+f"(d[0]),"+f"(d[1]),"+f"(d[2]),"+f"(d[3]),"+f"(d[4]),"+f"(d[5]),"+f"(d[6]),"+f"(d[7]),"+f"(d[8]),"+f"(d[9]),"+f"(d[10]),"+f"(d[11]),"+f"(d[12]),"+f"(d[13]),"+f"(d[14]),"+f"(d[15]),"+f"(d[16]),"+f"(d[17]),"+f"(d[18]),"+f"(d[19]),"+f"(d[20]),"+f"(d[21]),"+f"(d[22]),"+f"(d[23]) : "r"(a0),"r"(a1),"r"(a2),"r"(a3), "l"(db), "r"(sd), "n"(TB));
}
template<int TB> __device__ __forceinline__ void wgmma_rs_n56(float* d, uint32_t a0, uint32_t a1, uint32_t a2, uint32_t a3, uint64_t db, int sd){
  asm volatile("{ .reg .pred p; setp.ne.b32 p, %33, 0; wgmma.mma_async.sync.aligned.m64n56k16.f32.bf16.bf16 {%0,%1,%2,%3,%4,%5,%6,%7,%8,%9,%10,%11,%12,%13,%14,%15,%16,%17,%18,%19,%20,%21,%22,%23,%24,%25,%26,%27}, {%28,%29,%30,%31}, %32, p, 1, 1, %34; }"
   : "+f"(d[0]),"+f"(d[1]),"+f"(d[2]),"+f"(d[3]),"+f"(d[4]),"+f"(d[5]),"+f"(d[6]),"+f"(d[7]),"+f"(d[8]),"+f"(d[9]),"+f"(d[10]),"+f"(d[11]),"+f"(d[12]),"+f"(d[13]),"+f"(d[14]),"+f"(d[15]),"+f"(d[16]),"+f"(d[17]),"+f"(d[18]),"+f"(d[19]),"+f"(d[20]),"+f"(d[21]),"+f"(d[22]),"+f"(d[23]),"+f"(d[24]),"+f"(d[25]),"+f"(d[26]),"+f"(d[27]) : "r"(a0),"r"(a1),"r"(a2),"r"(a3), "l"(db), "r"(sd), "n"(TB));
}
template<int TB> __device__ __forceinline__ void wgmma_rs_n64(float* d, uint32_t a0, uint32_t a1, uint32_t a2, uint32_t a3, uint64_t db, int sd){
  asm volatile("{ .reg .pred p; setp.ne.b32 p, %37, 0; wgmma.mma_async.sync.aligned.m64n64k16.f32.bf16.bf16 {%0,%1,%2,%3,%4,%5,%6,%7,%8,%9,%10,%11,%12,%13,%14,%15,%16,%17,%18,%19,%20,%21,%22,%23,%24,%25,%26,%27,%28,%29,%30,%31}, {%32,%33,%34,%35}, %36, p, 1, 1, %38; }"
   : "+f"(d[0]),"+f"(d[1]),"+f"(d[2]),"+f"(d[3]),"+f"(d[4]),"+f"(d[5]),"+f"(d[6]),"+f"(d[7]),"+f"(d[8]),"+f"(d[9]),"+f"(d[10]),"+f"(d[11]),"+f"(d[12]),"+f"(d[13]),"+f"(d[14]),"+f"(d[15]),"+f"(d[16]),"+f"(d[17]),"+f"(d[18]),"+f"(d[19]),"+f"(d[20]),"+f"(d[21]),"+f"(d[22]),"+f"(d[23]),"+f"(d[24]),"+f"(d[25]),"+f"(d[26]),"+f"(d[27]),"+f"(d[28]),"+f"(d[29]),"+f"(d[30]),"+f"(d[31]) : "r"(a0),"r"(a1),"r"(a2),"r"(a3), "l"(db), "r"(sd), "n"(TB));
}
template<int N,int TA,int TB> __device__ __forceinline__ void wgmma_ss(float* d, uint64_t da, uint64_t db, int sd){
  if constexpr(N==176) wgmma_ss_n176<TA,TB>(d,da,db,sd);
}
template<int N,int TB> __device__ __forceinline__ void wgmma_rs(float* d, uint32_t a0,uint32_t a1,uint32_t a2,uint32_t a3, uint64_t db, int sd){
  if constexpr(N==8) wgmma_rs_n8<TB>(d,a0,a1,a2,a3,db,sd);
  if constexpr(N==16) wgmma_rs_n16<TB>(d,a0,a1,a2,a3,db,sd);
  if constexpr(N==24) wgmma_rs_n24<TB>(d,a0,a1,a2,a3,db,sd);
  if constexpr(N==32) wgmma_rs_n32<TB>(d,a0,a1,a2,a3,db,sd);
  if constexpr(N==40) wgmma_rs_n40<TB>(d,a0,a1,a2,a3,db,sd);
  if constexpr(N==48) wgmma_rs_n48<TB>(d,a0,a1,a2,a3,db,sd);
  if constexpr(N==56) wgmma_rs_n56<TB>(d,a0,a1,a2,a3,db,sd);
  if constexpr(N==64) wgmma_rs_n64<TB>(d,a0,a1,a2,a3,db,sd);
}


typedef __nv_bfloat16 bf16;
constexpr int S_ = 2048, D_ = 512, F_ = 1376, FS = 176;

__device__ __forceinline__ uint32_t smem_u32(const void* p){ return (uint32_t)__cvta_generic_to_shared(p); }
__device__ __forceinline__ void mbar_init(uint32_t bar, uint32_t cnt){ asm volatile("mbarrier.init.shared::cta.b64 [%0], %1;"::"r"(bar),"r"(cnt):"memory"); }
__device__ __forceinline__ void mbar_expect_tx(uint32_t bar, uint32_t bytes){ asm volatile("mbarrier.arrive.expect_tx.shared::cta.b64 _, [%0], %1;"::"r"(bar),"r"(bytes):"memory"); }
__device__ __forceinline__ void mbar_arrive(uint32_t bar){ asm volatile("mbarrier.arrive.shared::cta.b64 _, [%0];"::"r"(bar):"memory"); }
__device__ __forceinline__ void mbar_arrive_n(uint32_t bar, uint32_t n){ asm volatile("mbarrier.arrive.shared::cta.b64 _, [%0], %1;"::"r"(bar),"r"(n):"memory"); }
__device__ __forceinline__ void mbar_arrive_cl(uint32_t cbar){ asm volatile("mbarrier.arrive.shared::cluster.b64 _, [%0];"::"r"(cbar):"memory"); }
__device__ __forceinline__ uint32_t mapa(uint32_t a, uint32_t cta){ uint32_t r; asm volatile("mapa.shared::cluster.u32 %0, %1, %2;":"=r"(r):"r"(a),"r"(cta)); return r; }
__device__ __forceinline__ void mbar_wait(uint32_t bar, uint32_t ph){
  asm volatile("{ .reg .pred p; .reg .u32 c; mov.u32 c, 0;\n"
               "WL: mbarrier.try_wait.parity.shared::cta.b64 p, [%0], %1; @p bra WD; add.u32 c,c,1; setp.lt.u32 p, c, 1000000; @p bra WL; trap;\n"
               "WD: }"::"r"(bar),"r"(ph):"memory"); }
__device__ __forceinline__ uint32_t mbar_test(uint32_t bar, uint32_t ph){ uint32_t ok; asm volatile("{ .reg .pred p; mbarrier.test_wait.parity.shared::cta.b64 p, [%1], %2; selp.u32 %0,1,0,p; }":"=r"(ok):"r"(bar),"r"(ph):"memory"); return ok; }
__device__ __forceinline__ void spin_guard(int n){ asm volatile("{ .reg .pred p; setp.gt.s32 p, %0, 2000000; @p trap; }"::"r"(n)); }
__device__ __forceinline__ bool elect_one(){ uint32_t p; asm volatile("{ .reg .pred P; elect.sync _|P, 0xffffffff; selp.u32 %0,1,0,P; }":"=r"(p)); return p; }
__device__ __forceinline__ void tma2d(uint32_t dst, const CUtensorMap* m, int c0, int c1, uint32_t bar){
  asm volatile("cp.async.bulk.tensor.2d.shared::cluster.global.mbarrier::complete_tx::bytes [%0], [%1, {%3, %4}], [%2];"::"r"(dst),"l"(m),"r"(bar),"r"(c0),"r"(c1):"memory"); }
__device__ __forceinline__ void tma2d_mc(uint32_t dst, const CUtensorMap* m, int c0, int c1, uint32_t bar){
  asm volatile("cp.async.bulk.tensor.2d.shared::cluster.global.mbarrier::complete_tx::bytes.multicast::cluster [%0], [%1, {%3, %4}], [%2], %5;"::"r"(dst),"l"(m),"r"(bar),"r"(c0),"r"(c1),"h"((uint16_t)3):"memory"); }
__device__ __forceinline__ void wg_fence(){ asm volatile("wgmma.fence.sync.aligned;":::"memory"); }
__device__ __forceinline__ void wg_commit(){ asm volatile("wgmma.commit_group.sync.aligned;":::"memory"); }
template<int N> __device__ __forceinline__ void wg_wait(){ asm volatile("wgmma.wait_group.sync.aligned %0;"::"n"(N):"memory"); }
__device__ __forceinline__ uint64_t make_desc(uint32_t addr, uint32_t lbo, uint32_t sbo, uint32_t sw){ return (uint64_t)((addr&0x3FFFF)>>4) | ((uint64_t)((lbo&0x3FFFF)>>4)<<16) | ((uint64_t)((sbo&0x3FFFF)>>4)<<32) | ((uint64_t)sw<<62); }
__device__ __forceinline__ void ldsm4t(uint32_t a, uint32_t& r0, uint32_t& r1, uint32_t& r2, uint32_t& r3){ asm volatile("ldmatrix.sync.aligned.m8n8.x4.trans.shared.b16 {%0,%1,%2,%3}, [%4];":"=r"(r0),"=r"(r1),"=r"(r2),"=r"(r3):"r"(a):"memory"); }
__device__ __forceinline__ uint32_t pack_bf16(float lo, float hi){ uint32_t r; asm("cvt.rn.bf16x2.f32 %0, %1, %2;":"=r"(r):"f"(hi),"f"(lo)); return r; }
__device__ __forceinline__ float bf_lo(uint32_t v){ return __uint_as_float(v<<16); }
__device__ __forceinline__ float bf_hi(uint32_t v){ return __uint_as_float(v&0xffff0000u); }
__device__ __forceinline__ float rbf(float x){ return __bfloat162float(__float2bfloat16(x)); }
__device__ __forceinline__ uint32_t hadd2_bf16(uint32_t a, uint32_t b){ uint32_t r; asm("add.rn.bf16x2 %0, %1, %2;":"=r"(r):"r"(a),"r"(b)); return r; }
__device__ __forceinline__ float tanh_fast(float x){ float r; asm("tanh.approx.f32 %0, %1;":"=f"(r):"f"(x)); return r; }

__device__ __forceinline__ void st_rlx128(void* p, uint32_t a, uint32_t b, uint32_t c, uint32_t d){
  asm volatile("{ .reg .b64 l,h; .reg .b128 v; mov.b64 l,{%1,%2}; mov.b64 h,{%3,%4}; mov.b128 v,{l,h}; st.relaxed.gpu.global.b128 [%0], v; }"::"l"(p),"r"(a),"r"(b),"r"(c),"r"(d):"memory"); }
__device__ __forceinline__ void ld_rlx128(const void* p, uint4& v){
  asm volatile("{ .reg .b64 l,h; .reg .b128 v; ld.relaxed.gpu.global.b128 v, [%4]; mov.b128 {l,h}, v; mov.b64 {%0,%1}, l; mov.b64 {%2,%3}, h; }":"=r"(v.x),"=r"(v.y),"=r"(v.z),"=r"(v.w):"l"(p):"memory"); }
__device__ __forceinline__ void st_async128(uint32_t dst, uint32_t a, uint32_t b, uint32_t c, uint32_t d, uint32_t cbar){
  asm volatile("st.async.weak.shared::cluster.mbarrier::complete_tx::bytes.v4.b32 [%0], {%1,%2,%3,%4}, [%5];"::"r"(dst),"r"(a),"r"(b),"r"(c),"r"(d),"r"(cbar)); }
__device__ __forceinline__ void bulk_g2s(uint32_t dst, const void* src, uint32_t bytes, uint32_t bar){
  asm volatile("cp.async.bulk.shared::cluster.global.mbarrier::complete_tx::bytes [%0], [%1], %2, [%3];"::"r"(dst),"l"(src),"r"(bytes),"r"(bar):"memory"); }
__device__ __forceinline__ void lds128(uint32_t a, uint32_t& x, uint32_t& y, uint32_t& z, uint32_t& w){ asm volatile("ld.shared.v4.u32 {%0,%1,%2,%3}, [%4];":"=r"(x),"=r"(y),"=r"(z),"=r"(w):"r"(a):"memory"); }
__device__ __forceinline__ void tma4d_red_add(const CUtensorMap* m, int c0, int c1, int c2, int c3, uint32_t src){
  asm volatile("cp.reduce.async.bulk.tensor.4d.global.shared::cta.add.tile.bulk_group [%0, {%1, %2, %3, %4}], [%5];"::"l"(m),"r"(c0),"r"(c1),"r"(c2),"r"(c3),"r"(src):"memory"); }
__device__ __forceinline__ void stsm4_nm(uint32_t a, uint32_t r0, uint32_t r1, uint32_t r2, uint32_t r3){ asm volatile("stmatrix.sync.aligned.m8n8.x4.shared.b16 [%0], {%1,%2,%3,%4};"::"r"(a),"r"(r0),"r"(r1),"r"(r2),"r"(r3)); }
__device__ __forceinline__ void tma3d(uint32_t dst, const CUtensorMap* m, int c0, int c1, int c2, uint32_t bar){
  asm volatile("cp.async.bulk.tensor.3d.shared::cluster.global.mbarrier::complete_tx::bytes [%0], [%1, {%3, %4, %5}], [%2];"::"r"(dst),"l"(m),"r"(bar),"r"(c0),"r"(c1),"r"(c2):"memory"); }
__device__ __forceinline__ uint32_t lds32(uint32_t a){ uint32_t v; asm volatile("ld.shared.u32 %0, [%1];":"=r"(v):"r"(a)); return v; }
__device__ __forceinline__ void sts128(uint32_t a, uint32_t x, uint32_t y, uint32_t z, uint32_t w){ asm volatile("st.shared.v4.u32 [%0], {%1,%2,%3,%4};"::"r"(a),"r"(x),"r"(y),"r"(z),"r"(w):"memory"); }
__device__ __forceinline__ uint4 ldg_nc128(const void* p){ uint4 v; asm volatile("ld.global.nc.L1::no_allocate.v4.u32 {%0,%1,%2,%3}, [%4];":"=r"(v.x),"=r"(v.y),"=r"(v.z),"=r"(v.w):"l"(p)); return v; }
__device__ __forceinline__ uint32_t hmul2_bf16(uint32_t a, uint32_t b){ uint32_t r; asm("mul.rn.bf16x2 %0, %1, %2;":"=r"(r):"r"(a),"r"(b)); return r; }
__device__ __forceinline__ uint32_t hfma2_bf16(uint32_t a, uint32_t b, uint32_t c){ uint32_t r; asm("fma.rn.bf16x2 %0, %1, %2, %3;":"=r"(r):"r"(a),"r"(b),"r"(c)); return r; }
__device__ __forceinline__ uint32_t hsub2_bf16(uint32_t a, uint32_t b){ uint32_t r; asm("sub.rn.bf16x2 %0, %1, %2;":"=r"(r):"r"(a),"r"(b)); return r; }
__device__ __forceinline__ void signal_add(unsigned* p){ asm volatile("fence.acq_rel.gpu;":::"memory"); asm volatile("red.relaxed.gpu.global.add.u32 [%0], 1;"::"l"(p):"memory"); }
__device__ __forceinline__ void lds128_nm(uint32_t a, uint32_t& x, uint32_t& y, uint32_t& z, uint32_t& w){ asm volatile("ld.shared.v4.u32 {%0,%1,%2,%3}, [%4];":"=r"(x),"=r"(y),"=r"(z),"=r"(w):"r"(a)); }
__device__ __forceinline__ float ln_rstd(float var){
  float sq, r; asm("sqrt.approx.f32 %0, %1;":"=f"(sq):"f"(rbf(rbf(var)+1e-5f))); asm("rcp.approx.f32 %0, %1;":"=f"(r):"f"(rbf(sq))); return r; }
template<int N> __device__ __forceinline__ float4 gather_sum(const uint4* src, int stride, uint32_t par){
  uint4 v[N]; int it=0; uint32_t bad;
  do{
    bad=0;
    #pragma unroll
    for(int u=0;u<N;u++) ld_rlx128(src+u*stride, v[u]);
    #pragma unroll
    for(int u=0;u<N;u++) bad|=v[u].x^par;
    spin_guard(++it);
  }while(bad&1);
  float4 c=make_float4(0.f,0.f,0.f,0.f);
  #pragma unroll
  for(int u=0;u<N;u++){ c.x+=__uint_as_float(v[u].x); c.y+=__uint_as_float(v[u].y); c.z+=__uint_as_float(v[u].z); c.w+=__uint_as_float(v[u].w); }
  return c;
}
__host__ __device__ __forceinline__ int pos2row(int pos){
  const int P = 1 - (pos >> 10), thr = (pos & 1023) >> 3, k = (pos>>2)&1, h = (pos>>1)&1, e = pos&1;
  const int w = thr >> 5, tp = (thr >> 3)&3, j = (thr >> 1)&3, p = thr & 1;
  return 16*(127 - (64*P + 16*j + 8*k + 2*tp + e)) + 8*h + 2*w + p;
}

__device__ __align__(1024) bf16 g_hT[D_*S_];
__device__ __align__(1024) uint4 g_xa[128*128*8];
__device__ __align__(1024) uint4 g_qs[128*8];
__device__ uint4 g_stat[16*2*8*32];
__device__ uint4 g_csp[8*16*88];
__device__ uint4 g_cs2[8*96];
__device__ unsigned g_cnt[4*32];

constexpr int QDELAY = 2000, KV0 = 3, XAFTER = 5, XPOS = 3, ZKV = 3, WSTART = 6, W9 = 2, PACE = 3, CSLEEP = 600, SKW = 2, STX0 = 3, STX1 = 4, CSUN = 4, HF = 3, SSLEEP = 600, NIN = 7;
constexpr int CSU = CSUN;
constexpr uint32_t G2_CH = 0x33221010u, G2_PEER = 0xAC;
constexpr int NS = 6, WSLOT = 24576, NX = 4, XSLOT = 8192;
constexpr int OFF_RES0 = 0, OFF_X = 8192, OFF_RES1 = 73728, OFF_W = 81920;
constexpr int OFF_CS = OFF_W + NS*WSLOT, OFF_ROW = OFF_CS + 2*FS*4, OFF_BAR = OFF_ROW + 1024;
constexpr int TBL = 8320, UPL = 2112, UCH = 2*UPL, QP = 1088, KVCH = 4224;
constexpr int OFF_TBL = 32768, OFF_U = OFF_TBL + 4*TBL, OFF_XAL = 82944, OFF_XAE = OFF_W + 2*WSLOT;
constexpr int OFF_IMG = 0, OFF_X8 = OFF_XAL + 16384, OFF_ZB = OFF_W + WSLOT - 2048, EXB = 32*144;
#define KVOFF(T) (OFF_W + 3*WSLOT + (T)*KVCH - ((T)>>2)*(2*WSLOT+4*KVCH))
constexpr int OFF_KV = OFF_W + 3*WSLOT, OFF_Q = OFF_W + 4*WSLOT;
static_assert(OFF_X8 + EXB <= OFF_ZB && OFF_U + 4*UCH <= OFF_XAL && OFF_XAL + 16384 <= OFF_W + WSLOT, "overlay");
constexpr int B_WFULL = 0, B_WEMPTY = B_WFULL+NS, B_XFULL = B_WEMPTY+NS, B_XEMPTY = B_XFULL+2*NX, B_PRDY = B_XEMPTY+2*NX, B_AFULL = B_PRDY+2,
              B_ONE = B_AFULL+2, B_FB = B_ONE, B_INIT = B_FB+2, B_XA = B_INIT+2, B_PAR = B_XA+2, B_TD = B_PAR+2, B_KV = B_TD+1, B_U = B_KV+8, B_HD = B_U+8, B_Q = B_HD+2, B_QD = B_Q+8, B_SC = B_QD+1, B_X03 = B_SC+1, B_RT = B_X03+1, NBAR = B_RT+2;
constexpr int OFF_MISC = (OFF_BAR + NBAR*8 + 15)&~15;
constexpr int OFF_TGT = OFF_MISC + 16;
constexpr int SMEM_BYTES = OFF_TGT + 16;
static_assert(SMEM_BYTES<=232448,"smem");

struct Maps { CUtensorMap k, v, xa, w64, w48, wd, wd48, ht, out, out8; int upfirst; };

__device__ __forceinline__ void load_w_stage(const Maps& maps, uint32_t dst, int col, int k0, uint32_t fb){
  asm volatile("cp.async.bulk.tensor.4d.shared::cluster.global.mbarrier::complete_tx::bytes [%0], [%1, {%3, %4, %5, %5}], [%2];"::"r"(dst),"l"(&maps.w64),"r"(fb),"r"(col),"r"(k0),"r"(0):"memory");
  tma3d(dst+16384, &maps.w48, col+256-(int)(blockIdx.x&1)*80, k0, 0, fb);
}

template<int N> __device__ __forceinline__ void conv_mma(float* acc, const uint32_t* R, uint64_t db){
  wgmma_rs<N,0>(acc, R[0],R[1],R[2],R[3], db,   1);
  wgmma_rs<N,0>(acc, R[4],R[5],R[6],R[7], db+1, 1);
}
__device__ __forceinline__ void conv_lda(uint32_t* R, const uint32_t* tb, int off){
  R[0]=lds32(tb[0]+off); R[1]=lds32(tb[1]+off); R[3]=lds32(tb[2]+off); R[5]=lds32(tb[3]+off); R[7]=lds32(tb[4]+off);
}
__device__ __forceinline__ void conv_dup(uint32_t* R){
  asm volatile("mov.b32 %0, %1;":"=r"(R[2]):"r"(R[1])); asm volatile("mov.b32 %0, %1;":"=r"(R[4]):"r"(R[3])); asm volatile("mov.b32 %0, %1;":"=r"(R[6]):"r"(R[5]));
}
__device__ __forceinline__ void zero4(float* a){
  #pragma unroll
  for(int i=0;i<4;i+=2) asm volatile("mov.b64 {%0,%1}, 0;":"=f"(a[i]),"=f"(a[i+1]));
}
__device__ __forceinline__ uint32_t tid_now(){ uint32_t t; asm volatile("mov.u32 %0, %%tid.x;":"=r"(t)); return t; }
__device__ __forceinline__ void load_xs(uint4* x, uint4* st, uint32_t sb, int warp, int lane){
  const uint32_t tw = (warp&3)*32+lane, pc = ((warp>>2)*2)^(tw&7);
  #pragma unroll
  for(int i=0;i<4;i++) lds128(sb+OFF_XAL+tw*128+((pc^(i&1)^((i>>1)*4))<<4), x[i].x,x[i].y,x[i].z,x[i].w);
  #pragma unroll
  for(int i=0;i<8;i++) lds128(sb+OFF_XAE+tw*128+((i^(tw&7))<<4), st[i].x,st[i].y,st[i].z,st[i].w);
}
__device__ __forceinline__ void check_xs(uint4* x, uint4* st, uint32_t ep, uint32_t sb, int warp){
  for(int n=0;n<2000000;n++){
    uint32_t bad=0;
    #pragma unroll
    for(int i=0;i<8;i++) bad|=st[i].w^ep;
    if(!bad && x[0].x && x[1].x && x[2].x && x[3].x) break;
    const uint32_t t2=tid_now()&127, pc = ((warp>>2)*2)^(t2&7);
    #pragma unroll
    for(int i=0;i<4;i++) ld_rlx128(&g_xa[blockIdx.x*1024+t2*8+(pc^(i&1)^((i>>1)*4))], x[i]);
    #pragma unroll
    for(int i=0;i<8;i++) ld_rlx128(&g_qs[t2*8+(i^(t2&7))], st[i]);
  }
  __syncwarp();
}
__device__ __forceinline__ void ln_x(uint4* x, const uint4* st, uint4* a){
#define LNA(X,S) ({ const uint32_t d_=hsub2_bf16(X,S.x); hfma2_bf16(d_,S.y,hmul2_bf16(d_,S.z)); })
  #pragma unroll
  for(int i=0;i<2;i++){
    x[i].x=~x[i].x;
    a[i].x=LNA(x[i].x,st[0]); a[i].y=LNA(x[i].y,st[1]); a[i].z=LNA(x[i].z,st[2]); a[i].w=LNA(x[i].w,st[3]);
  }
}
template<int PART> __device__ __forceinline__ uint32_t ex_buf(uint32_t sb, int warp){
  return sb + (PART? (warp<7? OFF_IMG+warp*EXB : OFF_X8) : ((warp&3)<3? OFF_TBL+(warp>>2)*2*TBL+(warp&3)*EXB : OFF_XAL+(warp>>2)*EXB)); }
template<int PART> __device__ __forceinline__ void conv_put(const float* a0, const float* a1, uint4& e0, uint32_t sb, int warp, int lane){
  const uint32_t ad = ex_buf<PART>(sb,warp) + ((lane&24)|((lane&3)<<1)|((lane>>2)&1))*144;
  if(PART) sts128(ad+128, 0,0,0,0); else sts128(ad+128, e0.x,e0.y,e0.z,e0.w);
  #pragma unroll
  for(int ii=0;ii<8;ii++){
    const uint32_t w0=pack_bf16(a0[4*ii],a0[4*ii+1]), w1=pack_bf16(a0[4*ii+2],a0[4*ii+3]), w2=pack_bf16(a1[4*ii],a1[4*ii+1]), w3=pack_bf16(a1[4*ii+2],a1[4*ii+3]);
    sts128(ad+ii*16, w0,w1,w2,w3);
    if(PART && ii==0) e0=make_uint4(w0,w1,w2,w3);
  }
  __syncwarp();
}
template<int PART> __device__ __forceinline__ void conv_get(const uint4* x, const uint4* a, uint32_t sb, int warp, int lane){
  const int cb = blockIdx.x, chl = (warp>>2)*2;
  const uint32_t tw = (warp&3)*32+lane;
  const uint32_t eb = ex_buf<PART>(sb,warp) + (lane&1)*144 + (lane&6)*16 + (lane>>3)*288;
  uint4 d[4][2];
  #pragma unroll
  for(int c=0;c<4;c++){
    const uint32_t ad = eb + c*(8*144+288) - (((lane>>3)+c>3)? 4*288-16 : 0);
    lds128(ad, d[c][0].x,d[c][0].y,d[c][0].z,d[c][0].w);
    lds128(ad+16, d[c][1].x,d[c][1].y,d[c][1].z,d[c][1].w);
  }
#define SUM4(K,F) hadd2_bf16(hadd2_bf16(d[0][K].F,d[1][K].F),hadd2_bf16(d[2][K].F,d[3][K].F))
  uint4 o0, o1;
  o0.x=hadd2_bf16(x[0].x,hmul2_bf16(a[0].x,SUM4(0,x))); o0.y=hadd2_bf16(x[0].y,hmul2_bf16(a[0].y,SUM4(0,y)));
  o0.z=hadd2_bf16(x[0].z,hmul2_bf16(a[0].z,SUM4(1,x))); o0.w=hadd2_bf16(x[0].w,hmul2_bf16(a[0].w,SUM4(1,y)));
  o1.x=hadd2_bf16(x[1].x,hmul2_bf16(a[1].x,SUM4(0,z))); o1.y=hadd2_bf16(x[1].y,hmul2_bf16(a[1].y,SUM4(0,w)));
  o1.z=hadd2_bf16(x[1].z,hmul2_bf16(a[1].z,SUM4(1,z))); o1.w=hadd2_bf16(x[1].w,hmul2_bf16(a[1].w,SUM4(1,w)));
  uint4* dst = (uint4*)(g_hT + (cb*4+chl)*2048 + (1-PART)*1024) + tw;
  const uint32_t par = lds32(sb+OFF_MISC)&1;
  o0.x=(o0.x&~1u)|par; o1.x=(o1.x&~1u)|par;
  dst[0]=o0; dst[256]=o1;
}

__device__ __forceinline__ void x_check(uint32_t sb, uint32_t tile, int ch0, uint32_t par, int wg, int wq, int lane){
  const uint32_t d = tile+lane*128+(((2*wq)^(lane&7))<<4);
  if(__any_sync(~0u, ((lds32(d)^par)|(lds32(d+4096)^par))&1)){
    #pragma unroll 1
    for(int i=0;i<2;i++){
      const bf16* src = g_hT+(ch0+i*32+lane)*2048+wg*1024+(blockIdx.x>>3)*64+wq*16;
      uint4 v0, v1; int n=0;
      do{ ld_rlx128(src, v0); ld_rlx128(src+8, v1); }while((((v0.x^par)|(v1.x^par))&1) && ++n<2000000);
      sts128(d+i*4096, v0.x,v0.y,v0.z,v0.w); sts128((d+i*4096)^16, v1.x,v1.y,v1.z,v1.w);
    }
    asm volatile("fence.proxy.async.shared::cta;":::"memory");
    __syncwarp();
  }
}
__device__ __forceinline__ void first_x(const Maps& maps, uint32_t sb, int w){
  const int b = blockIdx.x, rank = b&1, rt = b>>3;
  const uint32_t bar = sb+OFF_BAR, xf = bar+8*(B_XFULL+w*NX), xd = sb+OFF_X+w*NX*XSLOT+rank*4096, rb = sb+(w? OFF_RES1:OFF_RES0);
  const int c0 = w*1024+rt*64, k0 = (rt>>1)+w*(SKW/2), cr = rank*256+((b>>1)&3)*64;
  mbar_expect_tx(xf, XSLOT); mbar_expect_tx(xf+8, 3*XSLOT); mbar_arrive(xf+16);
  const unsigned tgt = lds32(sb+OFF_TGT+(w? 0:12));
  mbar_wait(bar+8*(B_HD+w), 0);
  {
    unsigned v; int n=0;
    asm volatile("red.relaxed.gpu.global.add.u32 [%0], 1;"::"l"(&g_cnt[w? 0:96]):"memory");
    do{ asm volatile("ld.relaxed.gpu.global.u32 %0, [%1];":"=r"(v):"l"(&g_cnt[w? 0:96]):"memory"); }while((int)(v-tgt)<0 && ++n<2000000);
  }
  tma2d_mc(xd,         &maps.ht, c0, (k0&7)*64+rank*32,     xf);
  tma2d_mc(xd+XSLOT,   &maps.ht, c0, ((k0+1)&7)*64+rank*32, xf+8);
  tma2d_mc(xd+2*XSLOT, &maps.ht, c0, ((k0+2)&7)*64+rank*32, xf+8);
  tma2d(rb,      &maps.ht, c0, cr,    xf+8);
  tma2d(rb+4096, &maps.ht, c0, cr+32, xf+8);
}

__global__ void __cluster_dims__(2,1,1) __launch_bounds__(384,1)
fused_kernel(const __grid_constant__ Maps maps, const bf16* __restrict__ q, const bf16* __restrict__ shk, const bf16* __restrict__ ssmk,
             const bf16* __restrict__ ssmD, const bf16* __restrict__ wdn, bf16* __restrict__ out){
  extern __shared__ __align__(1024) uint8_t smem_raw[];
  if(threadIdx.x<32){ if(elect_one()){ asm volatile("cp.async.bulk.prefetch.L2.global [%0], 16384;"::"l"(q+blockIdx.x*8192)); } }
  unsigned c_begin; asm volatile("mov.u32 %0, %%clock;":"=r"(c_begin));
  const uint32_t sb = smem_u32(smem_raw);
  const int tid = threadIdx.x, lane = tid&31;
  const int warp = __shfl_sync(0xffffffffu, tid>>5, 0);
  const int wg = warp>>2;
  const int b = blockIdx.x, rank = b&1;
  const int f = b&7, rt = b>>3, fp = f>>1;
  const uint32_t bar = sb+OFF_BAR;

  if(wg==2){
    asm volatile("setmaxnreg.dec.sync.aligned.u32 56;");
    const int cg = b>>1;
    const int cb = cg*2+rank;
    unsigned epoch = 0; uint4 shw = make_uint4(0,0,0,0); uint2 dd = make_uint2(0,0);
    if(warp==11) asm volatile("ld.relaxed.gpu.global.u32 %0, [%1];":"=r"(epoch):"l"(&g_cnt[(lane&3)*32]));
    if(warp!=9){
      shw = ldg_nc128(shk + (cg*8+(lane&3)*2)*4);
      asm volatile("ld.global.nc.v2.u32 {%0,%1}, [%2];":"=r"(dd.x),"=r"(dd.y):"l"(ssmD + cb*4));
    }
    auto ldkv=[&](int i){
      const uint32_t fb=bar+8*(B_KV+i);
      mbar_expect_tx(fb, 2176+2048);
      tma3d(sb+KVOFF(i),      &maps.k, cg*8, i*32+rank*16-1, 0, fb);
      tma3d(sb+KVOFF(i)+2176, &maps.v, cg*8, i*32+rank*16,   0, fb);
    };
    if(warp==9){
      if(lane<3) asm volatile("prefetch.tensormap [%0];"::"l"(&maps.k+lane):"memory");
    }
    asm volatile("bar.sync 0;":::"memory");
    asm volatile("barrier.cluster.arrive.relaxed.aligned;":::"memory");
    if(warp==9){
      { unsigned c1; do{ asm volatile("mov.u32 %0, %%clock;":"=r"(c1)); }while(c1-c_begin<QDELAY); }
      if(elect_one()){
        #pragma unroll
        for(int i=0;i<KV0;i++) ldkv(i);
      }
      __syncwarp();
      mbar_wait(bar+8*B_QD, 0);
      if(elect_one()){
        asm volatile("cp.async.bulk.tensor.2d.global.shared::cta.bulk_group [%0, {%1, %2}], [%3];"::"l"(&maps.xa),"r"(b*64),"r"(0),"r"(sb+OFF_IMG):"memory");
        asm volatile("cp.async.bulk.commit_group;":::"memory");
        #pragma unroll 1
        for(int i=KV0;i<8;i++){
          ldkv(i);
          if(i==XAFTER){
            asm volatile("cp.async.bulk.wait_group.read 0;":::"memory");
            mbar_wait(bar+8*(B_KV+XPOS), 0);
            mbar_expect_tx(bar+8*B_XA, 32768); bulk_g2s(sb+OFF_XAL, &g_xa[cb*1024], 16384, bar+8*B_XA); bulk_g2s(sb+OFF_XAE, g_qs, 16384, bar+8*B_XA);
          }
        }
        mbar_wait(bar+8*B_WEMPTY, 0);
        mbar_wait(bar+8*(B_KV+ZKV), 0);
        #pragma unroll
        for(int i=0;i<8;i++) asm volatile("cp.async.bulk.global.shared::cta.bulk_group [%0], [%1], 2048;"::"l"(out+b*8192+i*1024),"r"(sb+OFF_ZB):"memory");
        asm volatile("cp.async.bulk.commit_group;":::"memory");
        mbar_wait(bar+8*(B_KV+WSTART), 0);
        #pragma unroll 1
        for(int it=0;it<W9;it++){
          mbar_wait(bar+8*(B_WEMPTY+it), 0);
          if(it>=PACE) mbar_wait(bar+8*(B_WFULL+it-PACE), 0);
          mbar_expect_tx(bar+8*(B_WFULL+it), 22528);
          load_w_stage(maps, sb+OFF_W+(5-it)*WSLOT, fp*352+rank*128, ((it+(rt&14))&15)*32, bar+8*(B_WFULL+it));
        }
        asm volatile("cp.async.bulk.wait_group 0;":::"memory");
        asm volatile("fence.proxy.async.global;":::"memory");
        mbar_arrive(bar+8*(B_HD+1));
      }
      __syncwarp();
    }
    if(warp==11){
      asm volatile("":"+r"(epoch));
      epoch = (epoch>>7)+1;
      if(lane<4) asm volatile("st.shared.u32 [%0], %1;"::"r"(sb+OFF_TGT+lane*4),"r"(epoch<<7):"memory");
      if(lane==0) sts128(sb+OFF_MISC, epoch, dd.x, dd.y, 0);
      __syncwarp();
      if(lane==0) mbar_arrive(bar+8*B_SC);
    }
    if(warp==8 && lane<7) asm volatile("prefetch.tensormap [%0];"::"l"(&maps.w64+lane):"memory");
    mbar_wait(bar+8*B_SC, 0);
    epoch = lds32(sb+OFF_MISC);
    const uint32_t par = epoch&1;
    auto ldx=[&](int w, int it){
      const uint32_t fb = bar+8*(B_XFULL+w*NX+(it&3));
      mbar_expect_tx(fb, XSLOT);
      tma2d_mc(sb+OFF_X+(w*NX+(it&3))*XSLOT+rank*4096, &maps.ht, w*1024+rt*64, ((it+(rt>>1)+w*(SKW/2))&7)*64+rank*32, fb);
    };
    if(warp!=9){
      const int cp = lane&3;
      uint32_t sw[4];
      { const uint4 w = shw;
        sw[0]=__byte_perm(w.x,w.z,0x5410); sw[1]=__byte_perm(w.x,w.z,0x7632); sw[2]=__byte_perm(w.y,w.w,0x5410); sw[3]=__byte_perm(w.y,w.w,0x7632); }
      const uint32_t udst = mapa(sb+OFF_U+(cp&1)*2*UCH, cp>>1), ubar = mapa(bar+8*B_U, cp>>1);
      asm volatile("barrier.cluster.wait.aligned;":::"memory");
      #pragma unroll 1
      for(int tk=(warp==8? 2:warp-10); tk<16; tk+=3){
        const int T=tk>>1, gl=(tk&1)*8+(lane>>2);
        mbar_wait(bar+8*(B_KV+T), 0);
        const uint32_t ka = sb+KVOFF(T)+gl*16+cp*4, va = ka+2176;
        uint32_t kk[11], u[8];
        #pragma unroll
        for(int r=0;r<3;r++) kk[r]=lds32(ka+(5+r)*272);
        #pragma unroll
        for(int r=0;r<8;r++){ kk[3+r]=lds32(ka+16+r*272); u[r]=lds32(va+r*256); }
        #pragma unroll
        for(int r=0;r<8;r++){
          uint32_t a=hmul2_bf16(kk[r],sw[3]); a=hadd2_bf16(a,hmul2_bf16(kk[r+1],sw[2])); a=hadd2_bf16(a,hmul2_bf16(kk[r+2],sw[1])); a=hadd2_bf16(a,hmul2_bf16(kk[r+3],sw[0]));
          u[r]=hmul2_bf16(a,u[r]);
        }
        const int R = 255-(T*32+rank*16+gl);
        const uint32_t d = udst + (R&1)*UPL + (R>>1)*16;
        st_async128(d,     __byte_perm(u[7],u[6],0x5410), __byte_perm(u[5],u[4],0x5410), __byte_perm(u[3],u[2],0x5410), __byte_perm(u[1],u[0],0x5410), ubar+8*T);
        st_async128(d+UCH, __byte_perm(u[7],u[6],0x7632), __byte_perm(u[5],u[4],0x7632), __byte_perm(u[3],u[2],0x7632), __byte_perm(u[1],u[0],0x7632), ubar+8*T);
      }
      __syncwarp();
      if(lane==0) mbar_arrive(bar+8*B_TD);
    } else {
      asm volatile("barrier.cluster.wait.aligned;":::"memory");
    }
    if(warp==8){
      if(elect_one()){
        const int col = fp*352+rank*128;
        #pragma unroll
        for(int it=W9; it<NS; it++){
          mbar_wait(bar+8*(B_WEMPTY+it), 0);
          if(it==4) mbar_wait(bar+8*B_TD, 0);
          if(it==5) mbar_wait(bar+8*(B_HD+1), 0);
          if(it>=PACE) mbar_wait(bar+8*(B_WFULL+it-PACE), 0);
          mbar_expect_tx(bar+8*(B_WFULL+it), 22528);
          load_w_stage(maps, sb+OFF_W+(5-it)*WSLOT, col, ((it+(rt&14))&15)*32, bar+8*(B_WFULL+it));
        }
        mbar_wait(bar+8*(B_INIT+1), 0);
        mbar_wait(bar+8*B_X03, 0); ldx(0,3);
        uint32_t wb = bar, dst = sb+OFF_W+5*WSLOT, ph = 1; int k0 = ((6+(rt&14))&15)*32;
        #pragma unroll 1
        for(int j=4; j<4+(10+SKW)/2; j++){
          mbar_wait(wb+8*B_WEMPTY, ph);
          mbar_expect_tx(wb, 22528);       load_w_stage(maps, dst, col, k0, wb);
          mbar_wait(wb+8*B_WEMPTY+8, ph);
          mbar_expect_tx(wb+8, 22528);     load_w_stage(maps, dst-WSLOT, col, k0+32, wb+8);
          if(j<8){ mbar_wait(bar+8*(B_XEMPTY+(j&3)), 0); ldx(0,j); }
          const int j1 = j-SKW/2;
          if(j1>=4 && j1<8){ if(j1==4) mbar_wait(bar+8*(B_FB+1), 0); mbar_wait(bar+8*(B_XEMPTY+NX+(j1&3)), 0); ldx(1,j1); }
          if(j==5) asm volatile("cp.async.bulk.prefetch.L2.global [%0], 11008;"::"l"(wdn+b*5504):"memory");
          const bool wrap = wb==bar+32;
          wb = wrap? bar : wb+16; dst = wrap? dst+4*WSLOT : dst-2*WSLOT; ph ^= wrap; k0 = (k0+64)&511;
        }
        #pragma unroll
        for(int j=0;j<8;j++){
          constexpr int I0=16+SKW;
          const int slot=(I0+j)%NS, ci=(G2_CH>>(4*j))&3, kh=((G2_PEER>>j)&1)^rank;
          mbar_wait(bar+8*(B_WEMPTY+slot), ((I0+j)/NS)&1);
          mbar_expect_tx(bar+8*(B_WFULL+slot), 22528);
          tma2d(sb+OFF_W+(5-slot)*WSLOT,       &maps.wd,   rank*256+((fp+ci)&3)*64, fp*352+kh*128,    bar+8*(B_WFULL+slot));
          tma2d(sb+OFF_W+(5-slot)*WSLOT+16384, &maps.wd48, rank*256+((fp+ci)&3)*64, fp*352+256+kh*48, bar+8*(B_WFULL+slot));
        }
      }
      __syncwarp();
    } else if(warp==11){
      if(elect_one()){
        #pragma unroll 1
        for(int w=0;w<2;w++){ first_x(maps, sb, w); }
        mbar_arrive(bar+8*(B_INIT+1));
      }
      __syncwarp();
      __nanosleep(CSLEEP);
      {
        const int j = rt*6+(lane>>2);
        float4 c = make_float4(0.f,0.f,0.f,0.f);
        if(lane<24 && j<88) c = gather_sum<4>(&g_csp[(f*16+(lane&3)*4)*88+j], 88, par);
        __syncwarp();
        #pragma unroll
        for(int o=1;o<4;o<<=1){ c.x+=__shfl_xor_sync(~0u,c.x,o); c.y+=__shfl_xor_sync(~0u,c.y,o); c.z+=__shfl_xor_sync(~0u,c.z,o); c.w+=__shfl_xor_sync(~0u,c.w,o); }
        if(lane<24 && j<88 && !(lane&3)) st_rlx128(&g_cs2[f*96+j], (__float_as_uint(c.x)&~1u)|par, __float_as_uint(c.y), __float_as_uint(c.z), __float_as_uint(c.w));
      }
      { uint4 v[3]; int n=0; const int j2 = lane<24? lane+64 : lane;
        do{ __nanosleep(CSLEEP); ld_rlx128(&g_cs2[f*96+lane], v[0]); ld_rlx128(&g_cs2[f*96+lane+32], v[1]); ld_rlx128(&g_cs2[f*96+j2], v[2]); spin_guard(++n); }while(((v[0].x^par)|(v[1].x^par)|(v[2].x^par))&1);
        *(uint4*)(smem_raw+OFF_CS+lane*16)=v[0]; *(uint4*)(smem_raw+OFF_CS+(lane+32)*16)=v[1]; *(uint4*)(smem_raw+OFF_CS+j2*16)=v[2]; }
      mbar_wait(bar+8*(B_FB+1), 0);
      __syncwarp();
      if(lane<2) mbar_arrive(bar+8*(B_PAR+lane));
      #pragma unroll 4
      for(int i=0;i<32;i++) g_xa[cb*1024+i*32+lane]=make_uint4(0,0,0,0);
    } else {
      const int w = warp-9;
      mbar_wait(bar+8*(B_HD+w), 0);
      if(elect_one()){
        const unsigned tgt = lds32(sb+OFF_TGT+4+4*w);
        signal_add(&g_cnt[32+32*w]);
        unsigned v; int n=0; do{ asm volatile("ld.acquire.gpu.global.u32 %0, [%1];":"=r"(v):"l"(&g_cnt[32+32*w]):"memory"); spin_guard(++n); }while((int)(v-tgt)<0);
        asm volatile("fence.proxy.async.global;":::"memory");
        if(w) ldx(1,3); else mbar_arrive(bar+8*B_X03);
        mbar_arrive(bar+8*(B_FB+w));
      }
      __syncwarp();
      mbar_wait(bar+8*(B_RT+w), 0);
      {
        __nanosleep(SSLEEP);
        const float4 st=gather_sum<8>(&g_stat[((rt*2+w)*8)*32+lane], 32, par);
        const float s0=st.x, q0=st.y, s1=st.z, q1=st.w;
        const float m0=s0*(1.f/512), m1=s1*(1.f/512);
        const float v0=fmaxf(q0*(1.f/512)-m0*m0,0.f), v1=fmaxf(q1*(1.f/512)-m1*m1,0.f);
        const float r0=ln_rstd(v0), r1=ln_rstd(v1);
        *(float4*)(smem_raw+OFF_ROW+w*512+lane*16)=make_float4(-rbf(m0),r0,-rbf(m1),r1);
        mbar_wait(bar+8*(B_XEMPTY+w*NX+3), 0);
        __syncwarp();
        if(lane==0) mbar_arrive(bar+8*(B_PAR+w));
      }
      if(elect_one()){
        const int orow = pos2row(w*1024+rt*64+53);
        #pragma unroll
        for(int c=0;c<HF;c++){
          mbar_wait(bar+8*(B_XEMPTY+w*NX+c), 1);
          tma4d_red_add(&maps.out8, rank*256+((fp+c)&3)*64, orow&7, (orow>>3)&15, orow>>7, sb+OFF_X+(w*NX+c)*XSLOT);
        }
        asm volatile("cp.async.bulk.commit_group;":::"memory");
        asm volatile("cp.async.bulk.wait_group.read 0;":::"memory");
      }
      __syncwarp();
    }
  } else {
    if(elect_one()){
      mbar_init(bar+8*(B_Q+warp),1);
      asm volatile("fence.proxy.async.shared::cta;":::"memory");
      mbar_expect_tx(bar+8*(B_Q+warp), 2048);
      const bf16* qp = q + pos2row((1-wg)*1024+b*8+(warp&3)*2)*512;
      bulk_g2s(sb+OFF_Q+2*warp*QP, qp, 1024, bar+8*(B_Q+warp)); bulk_g2s(sb+OFF_Q+(2*warp+1)*QP, qp-16*512, 1024, bar+8*(B_Q+warp));
    }
    __syncwarp();
    asm volatile("setmaxnreg.inc.sync.aligned.u32 224;");
    if(elect_one()){
      mbar_init(bar+8*(B_U+warp),1); mbar_expect_tx(bar+8*(B_U+warp), 2048);
      mbar_init(bar+8*(B_XFULL+warp),1); mbar_init(bar+8*(B_XEMPTY+warp),8);
      mbar_init(bar+8*(B_KV+warp),1);
      if(warp<NS){ mbar_init(bar+8*(B_WFULL+warp),1); mbar_init(bar+8*(B_WEMPTY+warp),8); mbar_init(bar+8*(B_ONE+warp),1); }
      else { const int i=warp-6; mbar_init(bar+8*(B_PRDY+i),4); mbar_init(bar+8*(B_RT+i),1); mbar_init(bar+8*(B_AFULL+i),1); mbar_expect_tx(bar+8*(B_AFULL+i), 22528); mbar_init(bar+8*(B_PAR+i),2); mbar_init(bar+8*(B_HD+i),8+i); if(i){ mbar_init(bar+8*B_SC,1); mbar_init(bar+8*B_X03,1); } else { mbar_init(bar+8*B_QD,8); mbar_init(bar+8*B_TD,3); } }
      asm volatile("fence.mbarrier_init.release.cluster;":::"memory");
    }
    __syncwarp();
    const int wq = warp&3, g = lane>>2, t = lane&3;
    if(tid<8){ sts128(sb+OFF_U+tid*UPL+128*16, 0,0,0,0); }
    if(tid<128) sts128(sb+OFF_ZB+tid*16, 0,0,0,0);
    if(tid<12){ sts128(sb+OFF_TBL+(tid&3)*TBL+(tid>>2)*16, 0,0,0,0); }
    uint4 kq[4]; uint32_t kn[4];
    #pragma unroll
    for(int i=0;i<4;i++){ kq[i]=ldg_nc128(ssmk+(b*4+i)*2048+tid*8); kn[i]=0; if(lane==31 && warp<7) asm volatile("ld.global.nc.u32 %0, [%1];":"=r"(kn[i]):"l"(ssmk+(b*4+i)*2048+tid*8+8)); }
    asm volatile("bar.sync 0;":::"memory");
    asm volatile("barrier.cluster.arrive.relaxed.aligned;":::"memory");
    #pragma unroll
    for(int i=0;i<4;i++) mbar_wait(bar+8*(B_Q+wg*4+i), 0);
    {
      const uint32_t la = sb+OFF_Q+(wg*8+2*(lane>>3)+(lane&1))*QP + ((lane&7)>>1)*16 + wq*256;
      uint4 tv[4];
      const int irow = wq*32+t*2+(g>>2);
      const uint32_t dst = sb+OFF_IMG+irow*128+(((((g&3)+4*wg)^(b&7))^(irow&7))<<4);
      #pragma unroll
      for(int i=0;i<4;i++) ldsm4t(la+i*64, tv[i].x,tv[i].y,tv[i].z,tv[i].w);
      #pragma unroll
      for(int i=0;i<4;i++) sts128(dst+i*1024, max(~tv[i].x,1u),tv[i].y,tv[i].z,tv[i].w);
      asm volatile("fence.proxy.async.shared::cta;":::"memory");
      __syncwarp();
      if(lane==0) mbar_arrive(bar+8*B_QD);
    }
    {
      uint32_t w[2][8];
      const uint32_t qa = sb+OFF_Q+(2*warp)*QP+lane*16;
      #pragma unroll
      for(int r=0;r<2;r++){ lds128_nm(qa+r*QP, w[r][0],w[r][1],w[r][2],w[r][3]); lds128_nm(qa+r*QP+512, w[r][4],w[r][5],w[r][6],w[r][7]); }
      float s[2], d[2];
      #pragma unroll
      for(int r=0;r<2;r++){
        float s0=0.f,s1=0.f,d0=0.f,d1=0.f;
        #pragma unroll
        for(int i=0;i<8;i++){ const float lo=bf_lo(w[r][i]), hi=bf_hi(w[r][i]); s0+=lo; s1+=hi; d0=fmaf(lo,lo,d0); d1=fmaf(hi,hi,d1); }
        s[r]=s0+s1; d[r]=d0+d1;
      }
      const bool u=lane&16, v=lane&8;
      const float a0=(u? s[1]:s[0])+__shfl_xor_sync(~0u,u? s[0]:s[1],16), a1=(u? d[1]:d[0])+__shfl_xor_sync(~0u,u? d[0]:d[1],16);
      float c0=(v? a1:a0)+__shfl_xor_sync(~0u,v? a0:a1,8);
      c0+=__shfl_xor_sync(~0u,c0,4); c0+=__shfl_xor_sync(~0u,c0,2); c0+=__shfl_xor_sync(~0u,c0,1);
      const float m=c0*(1.f/512), sq=__shfl_down_sync(~0u,c0,8);
      const float rs=ln_rstd(fmaxf(fmaf(-m,m,sq*(1.f/512)),0.f)), rh=rbf(rs);
      const float m1=__shfl_down_sync(~0u,m,16), rs1=__shfl_down_sync(~0u,rs,16), rh1=rbf(rs1);
      mbar_wait(bar+8*B_SC, 0);
      if(lane==0){ st_rlx128(&g_qs[b*8+(warp^(b&7))], pack_bf16(m,m1), pack_bf16(rh,rh1), pack_bf16(rs-rh,rs1-rh1), lds32(sb+OFF_MISC)); }
      __syncwarp();
    }
    mbar_wait(bar+8*B_SC, 0);
    {
      const int Q = tid+2;
      const uint32_t ta = sb+OFF_TBL+((Q*32)^(((Q>>2)&3)<<5));
      const bool sw2 = (Q>>2)&1;
      if(tid==0){
        const uint32_t d01=lds32(sb+OFF_MISC+4), d23=lds32(sb+OFF_MISC+8);
        kq[0].x=hadd2_bf16(kq[0].x,d01&0xffffu); kq[1].x=hadd2_bf16(kq[1].x,d01>>16); kq[2].x=hadd2_bf16(kq[2].x,d23&0xffffu); kq[3].x=hadd2_bf16(kq[3].x,d23>>16);
      }
      __syncwarp();
      #pragma unroll
      for(int i=0;i<4;i++){
        uint32_t nx = __shfl_down_sync(~0u, kq[i].x, 1); if(lane==31) nx = kn[i];
        const uint4 o = make_uint4(__byte_perm(kq[i].x,kq[i].y,0x5432), __byte_perm(kq[i].y,kq[i].z,0x5432), __byte_perm(kq[i].z,kq[i].w,0x5432), __byte_perm(kq[i].w,nx,0x5432));
        const uint4 f0 = sw2? o:kq[i], f1 = sw2? kq[i]:o;
        sts128(ta+i*TBL+(sw2?16:0), f0.x,f0.y,f0.z,f0.w);
        sts128(ta+i*TBL+(sw2?0:16), f1.x,f1.y,f1.z,f1.w);
        if(tid==0) sts128(sb+OFF_TBL+i*TBL+48, 0,0,0, kq[i].x<<16);
      }
      __syncwarp();
      asm volatile("bar.sync 1, 256;":::"memory");
    }
    __syncwarp();
    if(lane<3) mbar_arrive(bar+8*(B_WEMPTY+(lane==2? 4:lane)));
    asm volatile("barrier.cluster.wait.aligned;":::"memory");
    {
      const int c=lane>>3, p=g&1;
      uint32_t tb[5];
      #pragma unroll
      for(int s=0;s<5;s++){ const int y=16*c+wq+t+p+4*s; const int id=8*(y>>2)+4*(1-p)+(y&3); tb[s]=sb+OFF_TBL+wg*2*TBL+((id^(((id>>5)&3)<<3))<<2); }
      uint64_t du = make_desc(sb+OFF_U+wg*2*UCH, UPL, 128, 0);
      float aE[2][32], aL[2][32];
      uint32_t R[2][4][8], oku=0; uint4 xr[4], st[8], ar[2], e0;
#define P_TY(K) ((K)>=8 ? 2 : (K)&1)
#define P_LV(K) ((K)>=8 ? (K)-8 : (K)>>1)
#define P_MA(K) ((P_TY(K)==1 ? 15 : 7) - 2*P_LV(K))
#define P_N(K,M) (P_TY(K)==2 ? 64 : P_TY(K)==1 ? 128-8*(M) : 64-8*(M))
#define P_B(K,M) (8*(M) + (P_TY(K)==0 ? 64 : 0))
#define P_LD(K,J) conv_lda(R[(K)&1][J],tb,((J)&1)*TBL+(P_MA(K)-((J)>>1))*512)
#define P_MMA(K,J) conv_mma<P_N(K,P_MA(K)-((J)>>1))>(P_TY(K)==0? aE[(J)&1]:aL[(J)&1], R[(K)&1][J], du+((J)&1)*(UCH/16)+P_B(K,P_MA(K)-((J)>>1)))
#define CONV_PREP(K) { if constexpr(P_TY(K)!=1) oku = mbar_test(bar+8*(B_U+P_LV(K)+(P_TY(K)?4:0)),0); P_LD(K,0); P_LD(K,1); P_LD(K,2); P_LD(K,3); }
#define CONV_PAIR(K) { \
        _Pragma("unroll") for(int j=0;j<4;j++) conv_dup(R[(K)&1][j]); \
        if constexpr(P_TY(K)<2){ _Pragma("unroll") for(int i=0;i<2;i++){ float* a_=(P_TY(K)==0? aE[i]:aL[i])+8*P_LV(K); zero4(a_); zero4(a_+4); } } \
        if constexpr(P_TY(K)!=1){ if(!oku) mbar_wait(bar+8*(B_U+P_LV(K)+(P_TY(K)?4:0)),0); asm volatile("fence.proxy.async.shared::cta;":::"memory"); } \
        asm volatile("" : "+l"(du)); \
        PP_SYNC(); \
        wg_fence(); \
        P_MMA(K,0); P_MMA(K,1); \
        if constexpr(P_TY(K)<2){ wg_commit(); wg_fence(); } \
        P_MMA(K,2); P_MMA(K,3); \
        wg_commit(); \
        if((K)<11 || wg==0) PP_ARRIVE(); \
        if constexpr((K)<11){ if constexpr((K)>0){ if constexpr(P_TY(K)<2) wg_wait<2>(); else wg_wait<1>(); } if constexpr((K)!=6 && (K)!=0) CONV_PREP((K)+1) } }
#define PP_SYNC() asm volatile("bar.sync %0, 256;"::"r"(2+wg):"memory")
#define PP_ARRIVE() asm volatile("bar.arrive %0, 256;"::"r"(3-wg):"memory")
      if(wg==1) PP_ARRIVE();
      CONV_PREP(0) CONV_PREP(1) CONV_PAIR(0) CONV_PAIR(1) CONV_PAIR(2) CONV_PAIR(3) CONV_PAIR(4) CONV_PAIR(5)
      mbar_wait(bar+8*B_XA,0);
      wg_wait<0>();
      load_xs(xr,st,sb,warp,lane); check_xs(xr,st,lds32(sb+OFF_MISC),sb,warp); ln_x(xr+2,st+4,ar);
      if(lane==0) mbar_arrive(bar+8*(B_WEMPTY+3));
      CONV_PAIR(6)
      if(lane==0) mbar_arrive(bar+8*(B_WEMPTY+2));
      wg_wait<0>();
      conv_put<1>(aE[0],aE[1],e0,sb,warp,lane);
      CONV_PREP(7)
      conv_get<1>(xr+2,ar,sb,warp,lane);
      __syncwarp();
      if(lane==0) mbar_arrive(bar+8*B_HD);
      CONV_PAIR(7) CONV_PAIR(8) CONV_PAIR(9) CONV_PAIR(10) CONV_PAIR(11)
      ln_x(xr,st,ar);
      wg_wait<0>();
      conv_put<0>(aL[0],aL[1],e0,sb,warp,lane);
      conv_get<0>(xr,ar,sb,warp,lane);
      __syncwarp();
      if(lane==0){ mbar_arrive(bar+8*(B_HD+1)); mbar_arrive(bar+8*(B_WEMPTY+5)); }
    }
    if(wg==1 && wq<3){
      mbar_wait(bar+8*(B_WFULL+SKW+(rt&1)), 0);
      const int j = tid-128;
      const uint32_t par = lds32(sb+OFF_MISC)&1;
      float c0=0.f,c1=0.f,c2=0.f,c3=0.f;
      const uint32_t cb = sb+OFF_W+(5-SKW-(rt&1))*WSLOT+wq*8192+t*4+maps.upfirst*4096;
      #pragma unroll CSU
      for(int k=0;k<32;k++){
        const uint32_t ad = cb + k*128 + ((g^(k&7))<<4);
        const uint32_t v=lds32(ad), u=lds32(ad+4096-maps.upfirst*8192); c0+=bf_lo(v); c1+=bf_hi(v); c2+=bf_lo(u); c3+=bf_hi(u);
      }
      if(j<88) st_rlx128(&g_csp[(f*16+rt)*88+j], (__float_as_uint(c0)&~1u)|par, __float_as_uint(c1), __float_as_uint(c2), __float_as_uint(c3));
      __syncwarp();
    }
    const uint32_t xempty_cl = mapa(bar+8*(B_XEMPTY+wg*NX), lane&1);
    float ag[88], au[88];
    const uint32_t xbase = sb+OFF_X+wg*NX*XSLOT, rbase = sb+(wg? OFF_RES1:OFF_RES0);
    const uint32_t rfrag = rbase+((lane&7)+8*(lane>>4))*128+(((2*wq+((lane>>3)&1))^(lane&7))<<4);
    constexpr uint64_t DHI_A = (uint64_t)0x40000040u<<32, DHI_B = DHI_A | (512u<<16);
    const uint32_t og = maps.upfirst*256, ou = 256-og;
    uint32_t wb = bar+8*wg*(SKW%NS), ph = wg*(SKW/NS), dbl = (((sb+OFF_W+(5-wg*(SKW%NS))*WSLOT)&0x3FFFF)>>4), dal = (xbase&0x3FFFF)>>4, xb = bar+8*(B_XFULL+wg*NX), pwb = 0;
    uint32_t relm = lane==0? 0xff : lane==1? (wg? (0xff00>>(SKW/2))&0xff : (1<<(SKW/2))-1) : 0;
    const uint32_t lpar = lds32(sb+OFF_MISC);
    const int kx0 = (rt>>1)+wg*(SKW/2);
#define G1_STAGE(DA,DB,ACC) { wg_fence(); wgmma_ss<176,1,1>(ag, DA, DHI_B|((DB)+og), ACC); wgmma_ss<176,1,1>(au, DA, DHI_B|((DB)+ou), ACC); wgmma_ss<176,1,1>(ag, (DA)+128, DHI_B|((DB)+og+128), 1); wgmma_ss<176,1,1>(au, (DA)+128, DHI_B|((DB)+ou+128), 1); wg_commit(); }
    {
      mbar_wait(wb, ph); mbar_wait(xb, 0);
      x_check(sb, xbase, (kx0&7)*64, lpar, wg, wq, lane);
      #pragma unroll
      for(int i=0;i<88;i++){ ag[i]=0.f; au[i]=0.f; }
      G1_STAGE(DHI_A|dal, dbl, 0)
    }
    uint32_t okb = mbar_test(wb+8, ph);
    #pragma unroll 1
    for(int xi=0; xi<8; xi++){
      if(!okb) mbar_wait(wb+8, ph);
      G1_STAGE(DHI_A|(dal+256), dbl-WSLOT/16, 1)
      pwb = wb;
      const bool wrap = wb==bar+8*4;
      wb = wrap? bar : wb+16; dbl = wrap? dbl+4*(WSLOT/16) : dbl-2*(WSLOT/16); ph ^= wrap;
      dal = (xi==3)? dal-3*512 : dal+512; xb = (xi==3)? xb-24 : xb+8;
      const uint32_t oka = mbar_test(xb, xi>=3) & mbar_test(wb, ph);
      if(xi<2){ if(!oka) mbar_wait(xb, 0); x_check(sb, xbase+(xi+1)*XSLOT, ((kx0+xi+1)&7)*64, lpar, wg, wq, lane); }
      if(xi==(wg? STX1:STX0)){
        x_check(sb, rbase, rank*256+fp*64, lpar, wg, wq, lane);
        float s0=0.f,s1=0.f,q0=0.f,q1=0.f;
        #pragma unroll
        for(int kk=0;kk<4;kk++){
          uint32_t r[4]; ldsm4t(rfrag+kk*2048, r[0],r[1],r[2],r[3]);
          #pragma unroll
          for(int i=0;i<4;i++){ const float lo=bf_lo(r[i]), hi=bf_hi(r[i]); if(i&1){ s1+=lo+hi; q1=fmaf(lo,lo,fmaf(hi,hi,q1)); } else { s0+=lo+hi; q0=fmaf(lo,lo,fmaf(hi,hi,q0)); } }
        }
        #pragma unroll
        for(int o=1;o<4;o<<=1){ s0+=__shfl_xor_sync(~0u,s0,o); q0+=__shfl_xor_sync(~0u,q0,o); s1+=__shfl_xor_sync(~0u,s1,o); q1+=__shfl_xor_sync(~0u,q1,o); }
        if(t==0) st_rlx128(&g_stat[((rt*2+wg)*8+f)*32+wq*8+g], (__float_as_uint(s0)&~1u)|(lpar&1), __float_as_uint(q0), __float_as_uint(s1), __float_as_uint(q1));
        __syncwarp();
        if(tid==wg*128) mbar_arrive(bar+8*(B_RT+wg));
      }
      uint32_t rel = relm&1; relm>>=1; uint32_t xpar = xi>=3;
      asm volatile("":"+r"(rel),"+r"(xpar));
      wg_wait<1>();
      if(rel) mbar_arrive(pwb+8*B_WEMPTY);
      if(xi==7) break;
      if(!oka){ mbar_wait(xb, xpar); mbar_wait(wb, ph); }
      G1_STAGE(DHI_A|dal, dbl, 1)
      okb = mbar_test(wb+8, ph);
      wg_wait<1>();
      if(rel) mbar_arrive(pwb+8*B_WEMPTY+8);
      if((lane>>1)==1 && xi<4) mbar_arrive_cl(xempty_cl+8*xi);
      if(xi==6 && lane==0) mbar_arrive_cl(mapa(bar+8*(B_PRDY+wg), rank^1));
    }
    mbar_wait(bar+8*(B_PAR+wg), 0);
    mbar_wait(bar+8*(B_PRDY+wg), 0);
    const float4 p0=*(const float4*)(smem_raw+OFF_ROW+(wg*32+wq*8+g)*16);
    const float nm0=p0.x, r0=p0.y, nm1=p0.z, r1=p0.w;
    wg_wait<0>();
    if(lane==0){ mbar_arrive_n(pwb+8*B_WEMPTY+8, (wg && SKW)? 2:1); }
    uint32_t act[44], actp[44];
    const float sc0=0.5f*r0*r0, sc1=0.5f*r1*r1;
    const uint32_t adst = mapa(xbase+(3-wq)*2048+lane*16, rank^1), abar = mapa(bar+8*(B_AFULL+wg), rank^1);
    {
      const float4* cs = (const float4*)(smem_raw+OFF_CS);
      const float h0=0.5f*r0, h1=0.5f*r1;
      #pragma unroll
      for(int j=0;j<22;j++){
        const float4 c4=cs[4*j+t];
        const float g0=fmaf(nm0,c4.x,ag[4*j+0]), g1=fmaf(nm0,c4.y,ag[4*j+1]), g2=fmaf(nm1,c4.x,ag[4*j+2]), g3=fmaf(nm1,c4.y,ag[4*j+3]);
        const float y0=g0*fmaf(nm0,c4.z,au[4*j+0]), y1=g1*fmaf(nm0,c4.w,au[4*j+1]), y2=g2*fmaf(nm1,c4.z,au[4*j+2]), y3=g3*fmaf(nm1,c4.w,au[4*j+3]);
        act[2*j]  =pack_bf16(y0*fmaf(sc0,tanh_fast(g0*h0),sc0), y1*fmaf(sc0,tanh_fast(g1*h0),sc0));
        act[2*j+1]=pack_bf16(y2*fmaf(sc1,tanh_fast(g2*h1),sc1), y3*fmaf(sc1,tanh_fast(g3*h1),sc1));
        if((j%3)==2 && j/3<NIN){ const int kk=j/3; st_async128(adst+(kk>>2)*8192+(kk&3)*512, act[4*kk],act[4*kk+1],act[4*kk+2],act[4*kk+3], abar); }
      }
    }
    #pragma unroll
    for(int kk=NIN;kk<11;kk++) st_async128(adst+(kk>>2)*8192+(kk&3)*512, act[4*kk],act[4*kk+1],act[4*kk+2],act[4*kk+3], abar);
    float acc2[2][32];
    #pragma unroll
    for(int i=0;i<32;i++){ acc2[0][i]=0.f; acc2[1][i]=0.f; }
    const uint32_t wbase = xbase+(3-wq)*2048;
    const uint32_t srow = ((~lane&4)<<1) | ((~lane&1)<<2) | (lane&2) | ((lane>>3)&1);
    const int orow = pos2row(wg*1024+rt*64+wq*16+5);
    uint32_t hr[16];
    #pragma unroll
    for(int kk=0;kk<4;kk++) ldsm4t(rfrag+kk*2048, hr[4*kk],hr[4*kk+1],hr[4*kk+2],hr[4*kk+3]);
    auto stage=[&](const float* a, int c){
      #pragma unroll
      for(int kk=0;kk<4;kk++){
        uint32_t o0=pack_bf16(a[8*kk],a[8*kk+1]), o1=pack_bf16(a[8*kk+2],a[8*kk+3]), o2=pack_bf16(a[8*kk+4],a[8*kk+5]), o3=pack_bf16(a[8*kk+6],a[8*kk+7]);
        if(c==0){
          o0=hadd2_bf16(o0,hr[4*kk]); o1=hadd2_bf16(o1,hr[4*kk+1]); o2=hadd2_bf16(o2,hr[4*kk+2]); o3=hadd2_bf16(o3,hr[4*kk+3]);
        }
        stsm4_nm(wbase+c*8192+srow*128+(((2*kk+(lane>>4))^(srow&7))<<4), o0,o1,o2,o3);
      }
    };
    auto flush=[&](int c, int n){
      asm volatile("fence.proxy.async.shared::cta;":::"memory");
      __syncwarp();
      if(c<HF){ if(lane<2) mbar_arrive(bar+8*(B_XEMPTY+wg*NX+c)); }
      else if(elect_one()){
        tma4d_red_add(&maps.out, rank*256+((fp+c)&3)*64, orow&7, (orow>>3)&15, orow>>7, wbase+c*8192);
        asm volatile("cp.async.bulk.commit_group;":::"memory");
      }
    };
    uint32_t okw = 0;
    #pragma unroll
    for(int i=0;i<8;i++){
      const int ch = (G2_CH>>(4*i))&3, peer = (G2_PEER>>i)&1;
      constexpr int S0=(16+SKW)%NS, P0=((16+SKW)/NS)&1;
      const int slot=(S0+i)%NS, pslot=(S0+i+NS-1)%NS, ph=(P0+(S0+i)/NS)&1;
      if(i==2){
        mbar_wait(bar+8*(B_AFULL+wg), 0);
        #pragma unroll
        for(int kk=0;kk<11;kk++) lds128_nm(wbase+lane*16+(kk>>2)*8192+(kk&3)*512, actp[4*kk],actp[4*kk+1],actp[4*kk+2],actp[4*kk+3]);
      }
      if(!okw) mbar_wait(bar+8*(B_WFULL+slot), ph);
      if(i<7) okw = mbar_test(bar+8*(B_WFULL+(S0+i+1)%NS), (P0+(S0+i+1)/NS)&1);
      if(i==2 || i==4 || i==6 || (i==0 && wg==1)) asm volatile("bar.sync %0, 256;"::"r"(2+wg):"memory");
      const uint64_t db = make_desc(sb+OFF_W+(5-slot)*WSLOT, 0, 1024, 1);
      wg_fence();
      #pragma unroll
      for(int kk=0;kk<11;kk++){
        if(peer) wgmma_rs<64,1>(acc2[ch&1], actp[4*kk],actp[4*kk+1],actp[4*kk+2],actp[4*kk+3], db+kk*128, 1);
        else     wgmma_rs<64,1>(acc2[ch&1], act[4*kk],act[4*kk+1],act[4*kk+2],act[4*kk+3], db+kk*128, kk>0);
      }
      wg_commit();
      if(i==1 || i==3 || i==5 || (i==7 && wg==0)) asm volatile("bar.arrive %0, 256;"::"r"(3-wg):"memory");
      if(i==1){ wg_wait<0>(); if(lane<2) mbar_arrive(bar+8*(B_WEMPTY+(lane? slot:pslot))); }
      if(i==3){ wg_wait<1>(); stage(acc2[0], 0); flush(0,1); wg_wait<0>(); stage(acc2[1], 1); flush(1,1); }
      if(i==5){ wg_wait<0>(); stage(acc2[0], 2); flush(2,1); }
    }
    wg_wait<0>();
    stage(acc2[1], 3); flush(3,1);
    asm volatile("cp.async.bulk.wait_group.read 0;":::"memory");
  }
}

__device__ bf16 g_fb[S_*F_+2*S_*D_];
__device__ __forceinline__ float b2f_(bf16 x){ return __bfloat162float(x); }
__global__ void fb_ln(const bf16* x, bf16* y){
  __shared__ float red[16]; const int r=blockIdx.x, t=threadIdx.x; const float v=b2f_(x[r*512+t]);
  float s=v; for(int o=16;o;o>>=1) s+=__shfl_xor_sync(~0u,s,o); if((t&31)==0) red[t>>5]=s; __syncthreads(); s=0; for(int i=0;i<16;i++) s+=red[i]; const float m=s/512; __syncthreads();
  float d=(v-m)*(v-m); for(int o=16;o;o>>=1) d+=__shfl_xor_sync(~0u,d,o); if((t&31)==0) red[t>>5]=d; __syncthreads(); d=0; for(int i=0;i<16;i++) d+=red[i];
  y[r*512+t]=__float2bfloat16(rbf(v-rbf(m))/rbf(sqrtf(rbf(rbf(d/512)+1e-5f)))); }
__global__ void fb_kv(const bf16* k, const bf16* v, const bf16* sh, bf16* kv){ const int s=blockIdx.x, d=threadIdx.x; float a=0;
  for(int t=0;t<4;t++){ const int r=s+t-3; a=rbf(a+rbf((r>=0? b2f_(k[r*512+d]):0.f)*b2f_(sh[d*4+3-t]))); } kv[s*512+d]=__float2bfloat16(a*b2f_(v[s*512+d])); }
__global__ void fb_conv(const bf16* x, const bf16* qn, const bf16* kv, const bf16* K, const bf16* Dv, bf16* h){ const int s=blockIdx.x, d=threadIdx.x; float a=0;
  for(int j=0;j<=s;j++) a+=b2f_(K[d*2048+j])*b2f_(kv[(s-j)*512+d]);
  h[s*512+d]=__float2bfloat16(b2f_(x[s*512+d])+rbf(b2f_(qn[s*512+d])*rbf(rbf(a)+rbf(b2f_(kv[s*512+d])*b2f_(Dv[d]))))); }
__global__ void fb_g1(const bf16* xn, const bf16* wg, const bf16* wu, bf16* act){ const int s=blockIdx.x;
  for(int n=threadIdx.x;n<F_;n+=blockDim.x){ float g=0,u=0; for(int k=0;k<512;k++){ const float x=b2f_(xn[s*512+k]); g+=x*b2f_(wg[k*F_+n]); u+=x*b2f_(wu[k*F_+n]); }
    g=rbf(g); act[s*F_+n]=__float2bfloat16(rbf(g/(1.f+expf(-g)))*rbf(u)); } }
__global__ void fb_g2(const bf16* act, const bf16* wd, const bf16* h, bf16* out){ const int s=blockIdx.x, n=threadIdx.x; float a=0;
  for(int k=0;k<F_;k++) a+=b2f_(act[s*F_+k])*b2f_(wd[k*512+n]); out[s*512+n]=__float2bfloat16(b2f_(h[s*512+n])+rbf(a)); }

typedef CUresult (*PFN_encodeTiled)(CUtensorMap*, CUtensorMapDataType, cuuint32_t, void*, const cuuint64_t*, const cuuint64_t*, const cuuint32_t*, const cuuint32_t*, CUtensorMapInterleave, CUtensorMapSwizzle, CUtensorMapL2promotion, CUtensorMapFloatOOBfill);
static int g_enc_err;
static void make2d(PFN_encodeTiled enc, CUtensorMap* m, const void* p, uint64_t d0, uint64_t d1, uint32_t b0, uint32_t b1){
  cuuint64_t gd[2]={d0,d1}; cuuint64_t gs[1]={d0*2}; cuuint32_t bx[2]={b0,b1}; cuuint32_t es[2]={1,1};
  g_enc_err |= (int)enc(m,CU_TENSOR_MAP_DATA_TYPE_BFLOAT16,2,(void*)p,gd,gs,bx,es,CU_TENSOR_MAP_INTERLEAVE_NONE,CU_TENSOR_MAP_SWIZZLE_128B,CU_TENSOR_MAP_L2_PROMOTION_L2_128B,CU_TENSOR_MAP_FLOAT_OOB_FILL_NONE);
}
static void make3d(PFN_encodeTiled enc, CUtensorMap* m, const void* p, uint64_t d0, uint64_t d1, uint64_t d2, uint64_t s1, uint64_t s2, uint32_t b0, uint32_t b1, uint32_t b2, CUtensorMapSwizzle sw, CUtensorMapL2promotion pr){
  cuuint64_t gd[3]={d0,d1,d2}; cuuint64_t gs[2]={s1,s2}; cuuint32_t bx[3]={b0,b1,b2}; cuuint32_t es[3]={1,1,1};
  g_enc_err |= (int)enc(m,CU_TENSOR_MAP_DATA_TYPE_BFLOAT16,3,(void*)p,gd,gs,bx,es,CU_TENSOR_MAP_INTERLEAVE_NONE,sw,pr,CU_TENSOR_MAP_FLOAT_OOB_FILL_NONE);
}

extern "C" void kernel_launch(void* const* d_in, const int* in_sizes, int n_in, void* d_out, int out_size){
  const bf16* q=(const bf16*)d_in[0]; const bf16* k=(const bf16*)d_in[1]; const bf16* v=(const bf16*)d_in[2];
  const bf16* sh=(const bf16*)d_in[3]; const bf16* K=(const bf16*)d_in[4]; const bf16* Dv=(const bf16*)d_in[5];
  const bf16* wgt=(const bf16*)d_in[7]; const bf16* wup=(const bf16*)d_in[8]; const bf16* wdn=(const bf16*)d_in[9];
  void* fn=nullptr; cudaDriverEntryPointQueryResult qr; cudaGetDriverEntryPoint("cuTensorMapEncodeTiled",&fn,cudaEnableDefault,&qr);
  PFN_encodeTiled enc=(PFN_encodeTiled)fn;
  void* hT; cudaGetSymbolAddress(&hT,g_hT);
  Maps maps; g_enc_err = 0;
  make3d(enc,&maps.k,k,512,256,8,8192,1024,8,17,8,CU_TENSOR_MAP_SWIZZLE_NONE,CU_TENSOR_MAP_L2_PROMOTION_L2_128B);
  make3d(enc,&maps.v,v,512,256,8,8192,1024,8,16,8,CU_TENSOR_MAP_SWIZZLE_NONE,CU_TENSOR_MAP_L2_PROMOTION_L2_128B);
  { maps.upfirst = wup<wgt; const bf16* w0 = wup<wgt? wup:wgt; const uint64_t dm = (uint64_t)((wup<wgt? wgt-wup : wup-wgt)*2);
    cuuint64_t gd[4]={F_,D_,2,2}; cuuint64_t gs[3]={F_*2,dm,128}; cuuint32_t bx[4]={64,32,2,2}; cuuint32_t es[4]={1,1,1,1};
    g_enc_err |= (int)enc(&maps.w64,CU_TENSOR_MAP_DATA_TYPE_BFLOAT16,4,(void*)w0,gd,gs,bx,es,CU_TENSOR_MAP_INTERLEAVE_NONE,CU_TENSOR_MAP_SWIZZLE_128B,CU_TENSOR_MAP_L2_PROMOTION_L2_128B,CU_TENSOR_MAP_FLOAT_OOB_FILL_NONE);
    make3d(enc,&maps.w48,w0,F_,D_,2,F_*2,dm,48,32,2,CU_TENSOR_MAP_SWIZZLE_128B,CU_TENSOR_MAP_L2_PROMOTION_L2_128B); }
  make2d(enc,&maps.wd,wdn,D_,F_,64,128); make2d(enc,&maps.wd48,wdn,D_,F_,64,48);
  make2d(enc,&maps.ht,hT,S_,D_,64,32);
  { cuuint64_t gd[4]={512,8,16,16}; cuuint64_t gs[3]={1024,8192,131072}; cuuint32_t bx[4]={64,2,4,2}; cuuint32_t es[4]={1,1,1,1};
    g_enc_err |= (int)enc(&maps.out,CU_TENSOR_MAP_DATA_TYPE_BFLOAT16,4,d_out,gd,gs,bx,es,CU_TENSOR_MAP_INTERLEAVE_NONE,CU_TENSOR_MAP_SWIZZLE_128B,CU_TENSOR_MAP_L2_PROMOTION_NONE,CU_TENSOR_MAP_FLOAT_OOB_FILL_NONE);
    bx[3]=8; g_enc_err |= (int)enc(&maps.out8,CU_TENSOR_MAP_DATA_TYPE_BFLOAT16,4,d_out,gd,gs,bx,es,CU_TENSOR_MAP_INTERLEAVE_NONE,CU_TENSOR_MAP_SWIZZLE_128B,CU_TENSOR_MAP_L2_PROMOTION_NONE,CU_TENSOR_MAP_FLOAT_OOB_FILL_NONE); }
  void* xa; cudaGetSymbolAddress(&xa,g_xa);
  make2d(enc,&maps.xa,xa,8192,128,64,128);
  cudaFuncSetAttribute(fused_kernel,cudaFuncAttributeMaxDynamicSharedMemorySize,SMEM_BYTES);
  int ncl = 0;
  { cudaLaunchConfig_t cfg = {}; cfg.gridDim = dim3(128); cfg.blockDim = dim3(384); cfg.dynamicSmemBytes = SMEM_BYTES;
    cudaLaunchAttribute at[1]; at[0].id = cudaLaunchAttributeClusterDimension; at[0].val.clusterDim.x = 2; at[0].val.clusterDim.y = 1; at[0].val.clusterDim.z = 1;
    cfg.attrs = at; cfg.numAttrs = 1;
    if(cudaOccupancyMaxActiveClusters(&ncl, fused_kernel, &cfg) != cudaSuccess){ ncl = 0; (void)cudaGetLastError(); } }
  if(g_enc_err || ncl < 64){
    bf16* fb; cudaGetSymbolAddress((void**)&fb, g_fb); bf16 *ln=fb, *kv=fb+S_*D_, *act=fb+2*S_*D_;
    fb_ln<<<S_,512>>>(q,ln); fb_kv<<<S_,512>>>(k,v,sh,kv); fb_conv<<<S_,512>>>(q,ln,kv,K,Dv,(bf16*)hT); fb_ln<<<S_,512>>>((bf16*)hT,ln);
    fb_g1<<<S_,256>>>(ln,wgt,wup,act); fb_g2<<<S_,512>>>(act,wdn,(bf16*)hT,(bf16*)d_out);
    return;
  }
  fused_kernel<<<128,384,SMEM_BYTES>>>(maps,q,sh,K,Dv,wdn,(bf16*)d_out);
}
```
